```python
import torch

def _softmax(x, axis=-1):
    return torch.softmax(x, dim=axis)
def _gelu(x):
    return torch.nn.functional.gelu(x, approximate="tanh")
def _silu(x):
    return torch.nn.functional.silu(x)
def _sigmoid(x):
    return torch.sigmoid(x)
def _layernorm(x, axis=-1, eps=1e-5):
    m = x.mean(dim=axis, keepdim=True)
    v = x.var(dim=axis, keepdim=True, unbiased=False)
    return (x - m) / torch.sqrt(v + eps)
def _scatter_add(tgt, idx, src, axis=0):
    return tgt.clone().index_add_(axis, idx, src)
def _segment_sum(src, seg, n):
    out = torch.zeros((n,) + src.shape[1:], dtype=src.dtype)
    return out.index_add_(0, seg, src)
def _pad(x, pw):
    flat = tuple(v for pair in reversed(pw) for v in pair)
    return torch.nn.functional.pad(x, flat)

kernel_name = 'gated_mix__ssm_conv_h3__glu_gated_glu__prompt'

def setup_inputs():

    _w = (lambda a: (lambda t: t.to(torch.bfloat16) if t.is_floating_point() else t)(torch.as_tensor(a)))
    def _A_setup():
        B, S, D = 1, 2048, 640
        ks = 4
        return {
            "q": _w((lambda *s: torch.randn(*s, dtype=torch.bfloat16) * 0.05)(B, S, D)),
            "k": _w((lambda *s: torch.randn(*s, dtype=torch.bfloat16) * 0.4)(B, S, D)),
            "v": _w((lambda *s: torch.randn(*s, dtype=torch.bfloat16) * 0.4)(B, S, D)),
            "shift_k": _w((lambda *s: torch.randn(*s, dtype=torch.bfloat16) * 0.4)(D, ks) * 0.5),
            "ssm_k": _w((lambda *s: torch.randn(*s, dtype=torch.bfloat16) * 1.6)(D, S) * (1.0 / S ** 0.5)),
            "ssm_D": _w((lambda *s: torch.randn(*s, dtype=torch.bfloat16) * 0.4)(D)),
        }
    _A_in = _A_setup()

    def _B_setup():
        B, S, D, F = 1, 2048, 640, 1536
        return {
            "x": _w((lambda *s: torch.randn(*s, dtype=torch.bfloat16) * 0.05)(B, S, D)),
            "w_gate": _w((lambda *s: torch.randn(*s, dtype=torch.bfloat16) * 0.4)(D, F)),
            "w_up": _w((lambda *s: torch.randn(*s, dtype=torch.bfloat16) * 0.05)(D, F)),
            "w_down": _w((lambda *s: torch.randn(*s, dtype=torch.bfloat16) * 0.05)(F, D)),
        }
    _B_in = _B_setup()

    return {
        "A_q": _A_in["q"],
        "A_k": _A_in["k"],
        "A_v": _A_in["v"],
        "A_shift_k": _A_in["shift_k"],
        "A_ssm_k": _A_in["ssm_k"],
        "A_ssm_D": _A_in["ssm_D"],
        "B_x": _B_in["x"],
        "B_w_gate": _B_in["w_gate"],
        "B_w_up": _B_in["w_up"],
        "B_w_down": _B_in["w_down"],
        "gate_w": _w((lambda *s: torch.randn(*s, dtype=torch.bfloat16) * 0.05)(640) * 16.0),
    }

def reference(A_q, A_k, A_v, A_shift_k, A_ssm_k, A_ssm_D, B_x, B_w_gate, B_w_up, B_w_down, gate_w):
    def _A_ref(q, k, v, shift_k, ssm_k, ssm_D):
        B, S, D = q.shape
        ks = shift_k.shape[-1]
        k_pad = _pad(k, ((0, 0), (ks - 1, 0), (0, 0)))
        k_shift = torch.zeros_like(k)
        for t in range(ks):
            k_shift = k_shift + k_pad[:, t:t + S, :] * shift_k[:, ks - 1 - t][None, None, :]
        kv = k_shift * v
        L = 2 * S
        kv_pad = _pad(kv, ((0, 0), (0, S), (0, 0)))
        kf_pad = _pad(ssm_k, ((0, 0), (0, S)))
        kv_f = (lambda x, axes=(-2,-1): torch.fft.rfft2(x.float(), dim=axes))(kv_pad[:, None, :, :], axes=(1, 2))
        kf_f = (lambda x, axes=(-2,-1): torch.fft.rfft2(x.float(), dim=axes))(kf_pad[:, None, :], axes=(1, 2))
        kf_f = (lambda x, *d: x.permute(*d))(kf_f, 1, 2, 0)
        y_f = kv_f * kf_f[None, :, :, :]
        y = (lambda x, s, axes=(-2,-1): torch.fft.irfft2(x, s=s, dim=axes).to(torch.bfloat16))(y_f, (1, L), axes=(1, 2))[:, 0, :S, :]
        y = y + kv * ssm_D[None, None, :]
        return q * y

    def _B_ref(x, w_gate, w_up, w_down):
        g = torch.einsum("bsd,df->bsf", x, w_gate)
        u = torch.einsum("bsd,df->bsf", x, w_up)
        h = _sigmoid(g) * u
        return torch.einsum("bsf,fd->bsd", h, w_down)

    x = A_q
    g = _sigmoid((x * gate_w).sum(-1, keepdims=True))
    a = _A_ref(x, A_k, A_v, A_shift_k, A_ssm_k, A_ssm_D)
    b = _B_ref(x, B_w_gate, B_w_up, B_w_down)
    return g * a + (1 - g) * b
```

```cpp
#include <cuda_runtime.h>
#include <cuda.h>
#include <cuda_bf16.h>
#include <stdint.h>

namespace {

template<int TA, int TB> __device__ __forceinline__ void wgmma_n8(float* d, uint64_t da, uint64_t db, int sc) {
  asm volatile("{\n.reg .pred p;\nsetp.ne.b32 p, %6, 0;\n"
    "wgmma.mma_async.sync.aligned.m64n8k16.f32.bf16.bf16 {%0, %1, %2, %3}, %4, %5, p, 1, 1, %7, %8;\n}\n"
    : "+f"(d[0]), "+f"(d[1]), "+f"(d[2]), "+f"(d[3])
    : "l"(da), "l"(db), "r"(sc), "n"(TA), "n"(TB));
}
template<int TA, int TB> __device__ __forceinline__ void wgmma_n16(float* d, uint64_t da, uint64_t db, int sc) {
  asm volatile("{\n.reg .pred p;\nsetp.ne.b32 p, %10, 0;\n"
    "wgmma.mma_async.sync.aligned.m64n16k16.f32.bf16.bf16 {%0, %1, %2, %3, %4, %5, %6, %7}, %8, %9, p, 1, 1, %11, %12;\n}\n"
    : "+f"(d[0]), "+f"(d[1]), "+f"(d[2]), "+f"(d[3]), "+f"(d[4]), "+f"(d[5]), "+f"(d[6]), "+f"(d[7])
    : "l"(da), "l"(db), "r"(sc), "n"(TA), "n"(TB));
}
template<int TA, int TB> __device__ __forceinline__ void wgmma_n24(float* d, uint64_t da, uint64_t db, int sc) {
  asm volatile("{\n.reg .pred p;\nsetp.ne.b32 p, %14, 0;\n"
    "wgmma.mma_async.sync.aligned.m64n24k16.f32.bf16.bf16 {%0, %1, %2, %3, %4, %5, %6, %7, %8, %9, %10, %11}, %12, %13, p, 1, 1, %15, %16;\n}\n"
    : "+f"(d[0]), "+f"(d[1]), "+f"(d[2]), "+f"(d[3]), "+f"(d[4]), "+f"(d[5]), "+f"(d[6]), "+f"(d[7]), "+f"(d[8]), "+f"(d[9]), "+f"(d[10]), "+f"(d[11])
    : "l"(da), "l"(db), "r"(sc), "n"(TA), "n"(TB));
}
template<int TA, int TB> __device__ __forceinline__ void wgmma_n32(float* d, uint64_t da, uint64_t db, int sc) {
  asm volatile("{\n.reg .pred p;\nsetp.ne.b32 p, %18, 0;\n"
    "wgmma.mma_async.sync.aligned.m64n32k16.f32.bf16.bf16 {%0, %1, %2, %3, %4, %5, %6, %7, %8, %9, %10, %11, %12, %13, %14, %15}, %16, %17, p, 1, 1, %19, %20;\n}\n"
    : "+f"(d[0]), "+f"(d[1]), "+f"(d[2]), "+f"(d[3]), "+f"(d[4]), "+f"(d[5]), "+f"(d[6]), "+f"(d[7]), "+f"(d[8]), "+f"(d[9]), "+f"(d[10]), "+f"(d[11]), "+f"(d[12]), "+f"(d[13]), "+f"(d[14]), "+f"(d[15])
    : "l"(da), "l"(db), "r"(sc), "n"(TA), "n"(TB));
}
template<int TA, int TB> __device__ __forceinline__ void wgmma_n40(float* d, uint64_t da, uint64_t db, int sc) {
  asm volatile("{\n.reg .pred p;\nsetp.ne.b32 p, %22, 0;\n"
    "wgmma.mma_async.sync.aligned.m64n40k16.f32.bf16.bf16 {%0, %1, %2, %3, %4, %5, %6, %7, %8, %9, %10, %11, %12, %13, %14, %15, %16, %17, %18, %19}, %20, %21, p, 1, 1, %23, %24;\n}\n"
    : "+f"(d[0]), "+f"(d[1]), "+f"(d[2]), "+f"(d[3]), "+f"(d[4]), "+f"(d[5]), "+f"(d[6]), "+f"(d[7]), "+f"(d[8]), "+f"(d[9]), "+f"(d[10]), "+f"(d[11]), "+f"(d[12]), "+f"(d[13]), "+f"(d[14]), "+f"(d[15]), "+f"(d[16]), "+f"(d[17]), "+f"(d[18]), "+f"(d[19])
    : "l"(da), "l"(db), "r"(sc), "n"(TA), "n"(TB));
}
template<int TA, int TB> __device__ __forceinline__ void wgmma_n48(float* d, uint64_t da, uint64_t db, int sc) {
  asm volatile("{\n.reg .pred p;\nsetp.ne.b32 p, %26, 0;\n"
    "wgmma.mma_async.sync.aligned.m64n48k16.f32.bf16.bf16 {%0, %1, %2, %3, %4, %5, %6, %7, %8, %9, %10, %11, %12, %13, %14, %15, %16, %17, %18, %19, %20, %21, %22, %23}, %24, %25, p, 1, 1, %27, %28;\n}\n"
    : "+f"(d[0]), "+f"(d[1]), "+f"(d[2]), "+f"(d[3]), "+f"(d[4]), "+f"(d[5]), "+f"(d[6]), "+f"(d[7]), "+f"(d[8]), "+f"(d[9]), "+f"(d[10]), "+f"(d[11]), "+f"(d[12]), "+f"(d[13]), "+f"(d[14]), "+f"(d[15]), "+f"(d[16]), "+f"(d[17]), "+f"(d[18]), "+f"(d[19]), "+f"(d[20]), "+f"(d[21]), "+f"(d[22]), "+f"(d[23])
    : "l"(da), "l"(db), "r"(sc), "n"(TA), "n"(TB));
}
template<int TA, int TB> __device__ __forceinline__ void wgmma_n56(float* d, uint64_t da, uint64_t db, int sc) {
  asm volatile("{\n.reg .pred p;\nsetp.ne.b32 p, %30, 0;\n"
    "wgmma.mma_async.sync.aligned.m64n56k16.f32.bf16.bf16 {%0, %1, %2, %3, %4, %5, %6, %7, %8, %9, %10, %11, %12, %13, %14, %15, %16, %17, %18, %19, %20, %21, %22, %23, %24, %25, %26, %27}, %28, %29, p, 1, 1, %31, %32;\n}\n"
    : "+f"(d[0]), "+f"(d[1]), "+f"(d[2]), "+f"(d[3]), "+f"(d[4]), "+f"(d[5]), "+f"(d[6]), "+f"(d[7]), "+f"(d[8]), "+f"(d[9]), "+f"(d[10]), "+f"(d[11]), "+f"(d[12]), "+f"(d[13]), "+f"(d[14]), "+f"(d[15]), "+f"(d[16]), "+f"(d[17]), "+f"(d[18]), "+f"(d[19]), "+f"(d[20]), "+f"(d[21]), "+f"(d[22]), "+f"(d[23]), "+f"(d[24]), "+f"(d[25]), "+f"(d[26]), "+f"(d[27])
    : "l"(da), "l"(db), "r"(sc), "n"(TA), "n"(TB));
}
template<int TA, int TB> __device__ __forceinline__ void wgmma_n64(float* d, uint64_t da, uint64_t db, int sc) {
  asm volatile("{\n.reg .pred p;\nsetp.ne.b32 p, %34, 0;\n"
    "wgmma.mma_async.sync.aligned.m64n64k16.f32.bf16.bf16 {%0, %1, %2, %3, %4, %5, %6, %7, %8, %9, %10, %11, %12, %13, %14, %15, %16, %17, %18, %19, %20, %21, %22, %23, %24, %25, %26, %27, %28, %29, %30, %31}, %32, %33, p, 1, 1, %35, %36;\n}\n"
    : "+f"(d[0]), "+f"(d[1]), "+f"(d[2]), "+f"(d[3]), "+f"(d[4]), "+f"(d[5]), "+f"(d[6]), "+f"(d[7]), "+f"(d[8]), "+f"(d[9]), "+f"(d[10]), "+f"(d[11]), "+f"(d[12]), "+f"(d[13]), "+f"(d[14]), "+f"(d[15]), "+f"(d[16]), "+f"(d[17]), "+f"(d[18]), "+f"(d[19]), "+f"(d[20]), "+f"(d[21]), "+f"(d[22]), "+f"(d[23]), "+f"(d[24]), "+f"(d[25]), "+f"(d[26]), "+f"(d[27]), "+f"(d[28]), "+f"(d[29]), "+f"(d[30]), "+f"(d[31])
    : "l"(da), "l"(db), "r"(sc), "n"(TA), "n"(TB));
}
template<int TA, int TB> __device__ __forceinline__ void wgmma_n72(float* d, uint64_t da, uint64_t db, int sc) {
  asm volatile("{\n.reg .pred p;\nsetp.ne.b32 p, %38, 0;\n"
    "wgmma.mma_async.sync.aligned.m64n72k16.f32.bf16.bf16 {%0, %1, %2, %3, %4, %5, %6, %7, %8, %9, %10, %11, %12, %13, %14, %15, %16, %17, %18, %19, %20, %21, %22, %23, %24, %25, %26, %27, %28, %29, %30, %31, %32, %33, %34, %35}, %36, %37, p, 1, 1, %39, %40;\n}\n"
    : "+f"(d[0]), "+f"(d[1]), "+f"(d[2]), "+f"(d[3]), "+f"(d[4]), "+f"(d[5]), "+f"(d[6]), "+f"(d[7]), "+f"(d[8]), "+f"(d[9]), "+f"(d[10]), "+f"(d[11]), "+f"(d[12]), "+f"(d[13]), "+f"(d[14]), "+f"(d[15]), "+f"(d[16]), "+f"(d[17]), "+f"(d[18]), "+f"(d[19]), "+f"(d[20]), "+f"(d[21]), "+f"(d[22]), "+f"(d[23]), "+f"(d[24]), "+f"(d[25]), "+f"(d[26]), "+f"(d[27]), "+f"(d[28]), "+f"(d[29]), "+f"(d[30]), "+f"(d[31]), "+f"(d[32]), "+f"(d[33]), "+f"(d[34]), "+f"(d[35])
    : "l"(da), "l"(db), "r"(sc), "n"(TA), "n"(TB));
}
template<int TA, int TB> __device__ __forceinline__ void wgmma_n80(float* d, uint64_t da, uint64_t db, int sc) {
  asm volatile("{\n.reg .pred p;\nsetp.ne.b32 p, %42, 0;\n"
    "wgmma.mma_async.sync.aligned.m64n80k16.f32.bf16.bf16 {%0, %1, %2, %3, %4, %5, %6, %7, %8, %9, %10, %11, %12, %13, %14, %15, %16, %17, %18, %19, %20, %21, %22, %23, %24, %25, %26, %27, %28, %29, %30, %31, %32, %33, %34, %35, %36, %37, %38, %39}, %40, %41, p, 1, 1, %43, %44;\n}\n"
    : "+f"(d[0]), "+f"(d[1]), "+f"(d[2]), "+f"(d[3]), "+f"(d[4]), "+f"(d[5]), "+f"(d[6]), "+f"(d[7]), "+f"(d[8]), "+f"(d[9]), "+f"(d[10]), "+f"(d[11]), "+f"(d[12]), "+f"(d[13]), "+f"(d[14]), "+f"(d[15]), "+f"(d[16]), "+f"(d[17]), "+f"(d[18]), "+f"(d[19]), "+f"(d[20]), "+f"(d[21]), "+f"(d[22]), "+f"(d[23]), "+f"(d[24]), "+f"(d[25]), "+f"(d[26]), "+f"(d[27]), "+f"(d[28]), "+f"(d[29]), "+f"(d[30]), "+f"(d[31]), "+f"(d[32]), "+f"(d[33]), "+f"(d[34]), "+f"(d[35]), "+f"(d[36]), "+f"(d[37]), "+f"(d[38]), "+f"(d[39])
    : "l"(da), "l"(db), "r"(sc), "n"(TA), "n"(TB));
}
template<int TA, int TB> __device__ __forceinline__ void wgmma_n88(float* d, uint64_t da, uint64_t db, int sc) {
  asm volatile("{\n.reg .pred p;\nsetp.ne.b32 p, %46, 0;\n"
    "wgmma.mma_async.sync.aligned.m64n88k16.f32.bf16.bf16 {%0, %1, %2, %3, %4, %5, %6, %7, %8, %9, %10, %11, %12, %13, %14, %15, %16, %17, %18, %19, %20, %21, %22, %23, %24, %25, %26, %27, %28, %29, %30, %31, %32, %33, %34, %35, %36, %37, %38, %39, %40, %41, %42, %43}, %44, %45, p, 1, 1, %47, %48;\n}\n"
    : "+f"(d[0]), "+f"(d[1]), "+f"(d[2]), "+f"(d[3]), "+f"(d[4]), "+f"(d[5]), "+f"(d[6]), "+f"(d[7]), "+f"(d[8]), "+f"(d[9]), "+f"(d[10]), "+f"(d[11]), "+f"(d[12]), "+f"(d[13]), "+f"(d[14]), "+f"(d[15]), "+f"(d[16]), "+f"(d[17]), "+f"(d[18]), "+f"(d[19]), "+f"(d[20]), "+f"(d[21]), "+f"(d[22]), "+f"(d[23]), "+f"(d[24]), "+f"(d[25]), "+f"(d[26]), "+f"(d[27]), "+f"(d[28]), "+f"(d[29]), "+f"(d[30]), "+f"(d[31]), "+f"(d[32]), "+f"(d[33]), "+f"(d[34]), "+f"(d[35]), "+f"(d[36]), "+f"(d[37]), "+f"(d[38]), "+f"(d[39]), "+f"(d[40]), "+f"(d[41]), "+f"(d[42]), "+f"(d[43])
    : "l"(da), "l"(db), "r"(sc), "n"(TA), "n"(TB));
}
template<int TA, int TB> __device__ __forceinline__ void wgmma_n96(float* d, uint64_t da, uint64_t db, int sc) {
  asm volatile("{\n.reg .pred p;\nsetp.ne.b32 p, %50, 0;\n"
    "wgmma.mma_async.sync.aligned.m64n96k16.f32.bf16.bf16 {%0, %1, %2, %3, %4, %5, %6, %7, %8, %9, %10, %11, %12, %13, %14, %15, %16, %17, %18, %19, %20, %21, %22, %23, %24, %25, %26, %27, %28, %29, %30, %31, %32, %33, %34, %35, %36, %37, %38, %39, %40, %41, %42, %43, %44, %45, %46, %47}, %48, %49, p, 1, 1, %51, %52;\n}\n"
    : "+f"(d[0]), "+f"(d[1]), "+f"(d[2]), "+f"(d[3]), "+f"(d[4]), "+f"(d[5]), "+f"(d[6]), "+f"(d[7]), "+f"(d[8]), "+f"(d[9]), "+f"(d[10]), "+f"(d[11]), "+f"(d[12]), "+f"(d[13]), "+f"(d[14]), "+f"(d[15]), "+f"(d[16]), "+f"(d[17]), "+f"(d[18]), "+f"(d[19]), "+f"(d[20]), "+f"(d[21]), "+f"(d[22]), "+f"(d[23]), "+f"(d[24]), "+f"(d[25]), "+f"(d[26]), "+f"(d[27]), "+f"(d[28]), "+f"(d[29]), "+f"(d[30]), "+f"(d[31]), "+f"(d[32]), "+f"(d[33]), "+f"(d[34]), "+f"(d[35]), "+f"(d[36]), "+f"(d[37]), "+f"(d[38]), "+f"(d[39]), "+f"(d[40]), "+f"(d[41]), "+f"(d[42]), "+f"(d[43]), "+f"(d[44]), "+f"(d[45]), "+f"(d[46]), "+f"(d[47])
    : "l"(da), "l"(db), "r"(sc), "n"(TA), "n"(TB));
}
template<int TA, int TB> __device__ __forceinline__ void wgmma_n104(float* d, uint64_t da, uint64_t db, int sc) {
  asm volatile("{\n.reg .pred p;\nsetp.ne.b32 p, %54, 0;\n"
    "wgmma.mma_async.sync.aligned.m64n104k16.f32.bf16.bf16 {%0, %1, %2, %3, %4, %5, %6, %7, %8, %9, %10, %11, %12, %13, %14, %15, %16, %17, %18, %19, %20, %21, %22, %23, %24, %25, %26, %27, %28, %29, %30, %31, %32, %33, %34, %35, %36, %37, %38, %39, %40, %41, %42, %43, %44, %45, %46, %47, %48, %49, %50, %51}, %52, %53, p, 1, 1, %55, %56;\n}\n"
    : "+f"(d[0]), "+f"(d[1]), "+f"(d[2]), "+f"(d[3]), "+f"(d[4]), "+f"(d[5]), "+f"(d[6]), "+f"(d[7]), "+f"(d[8]), "+f"(d[9]), "+f"(d[10]), "+f"(d[11]), "+f"(d[12]), "+f"(d[13]), "+f"(d[14]), "+f"(d[15]), "+f"(d[16]), "+f"(d[17]), "+f"(d[18]), "+f"(d[19]), "+f"(d[20]), "+f"(d[21]), "+f"(d[22]), "+f"(d[23]), "+f"(d[24]), "+f"(d[25]), "+f"(d[26]), "+f"(d[27]), "+f"(d[28]), "+f"(d[29]), "+f"(d[30]), "+f"(d[31]), "+f"(d[32]), "+f"(d[33]), "+f"(d[34]), "+f"(d[35]), "+f"(d[36]), "+f"(d[37]), "+f"(d[38]), "+f"(d[39]), "+f"(d[40]), "+f"(d[41]), "+f"(d[42]), "+f"(d[43]), "+f"(d[44]), "+f"(d[45]), "+f"(d[46]), "+f"(d[47]), "+f"(d[48]), "+f"(d[49]), "+f"(d[50]), "+f"(d[51])
    : "l"(da), "l"(db), "r"(sc), "n"(TA), "n"(TB));
}
template<int TA, int TB> __device__ __forceinline__ void wgmma_n112(float* d, uint64_t da, uint64_t db, int sc) {
  asm volatile("{\n.reg .pred p;\nsetp.ne.b32 p, %58, 0;\n"
    "wgmma.mma_async.sync.aligned.m64n112k16.f32.bf16.bf16 {%0, %1, %2, %3, %4, %5, %6, %7, %8, %9, %10, %11, %12, %13, %14, %15, %16, %17, %18, %19, %20, %21, %22, %23, %24, %25, %26, %27, %28, %29, %30, %31, %32, %33, %34, %35, %36, %37, %38, %39, %40, %41, %42, %43, %44, %45, %46, %47, %48, %49, %50, %51, %52, %53, %54, %55}, %56, %57, p, 1, 1, %59, %60;\n}\n"
    : "+f"(d[0]), "+f"(d[1]), "+f"(d[2]), "+f"(d[3]), "+f"(d[4]), "+f"(d[5]), "+f"(d[6]), "+f"(d[7]), "+f"(d[8]), "+f"(d[9]), "+f"(d[10]), "+f"(d[11]), "+f"(d[12]), "+f"(d[13]), "+f"(d[14]), "+f"(d[15]), "+f"(d[16]), "+f"(d[17]), "+f"(d[18]), "+f"(d[19]), "+f"(d[20]), "+f"(d[21]), "+f"(d[22]), "+f"(d[23]), "+f"(d[24]), "+f"(d[25]), "+f"(d[26]), "+f"(d[27]), "+f"(d[28]), "+f"(d[29]), "+f"(d[30]), "+f"(d[31]), "+f"(d[32]), "+f"(d[33]), "+f"(d[34]), "+f"(d[35]), "+f"(d[36]), "+f"(d[37]), "+f"(d[38]), "+f"(d[39]), "+f"(d[40]), "+f"(d[41]), "+f"(d[42]), "+f"(d[43]), "+f"(d[44]), "+f"(d[45]), "+f"(d[46]), "+f"(d[47]), "+f"(d[48]), "+f"(d[49]), "+f"(d[50]), "+f"(d[51]), "+f"(d[52]), "+f"(d[53]), "+f"(d[54]), "+f"(d[55])
    : "l"(da), "l"(db), "r"(sc), "n"(TA), "n"(TB));
}
template<int TA, int TB> __device__ __forceinline__ void wgmma_n120(float* d, uint64_t da, uint64_t db, int sc) {
  asm volatile("{\n.reg .pred p;\nsetp.ne.b32 p, %62, 0;\n"
    "wgmma.mma_async.sync.aligned.m64n120k16.f32.bf16.bf16 {%0, %1, %2, %3, %4, %5, %6, %7, %8, %9, %10, %11, %12, %13, %14, %15, %16, %17, %18, %19, %20, %21, %22, %23, %24, %25, %26, %27, %28, %29, %30, %31, %32, %33, %34, %35, %36, %37, %38, %39, %40, %41, %42, %43, %44, %45, %46, %47, %48, %49, %50, %51, %52, %53, %54, %55, %56, %57, %58, %59}, %60, %61, p, 1, 1, %63, %64;\n}\n"
    : "+f"(d[0]), "+f"(d[1]), "+f"(d[2]), "+f"(d[3]), "+f"(d[4]), "+f"(d[5]), "+f"(d[6]), "+f"(d[7]), "+f"(d[8]), "+f"(d[9]), "+f"(d[10]), "+f"(d[11]), "+f"(d[12]), "+f"(d[13]), "+f"(d[14]), "+f"(d[15]), "+f"(d[16]), "+f"(d[17]), "+f"(d[18]), "+f"(d[19]), "+f"(d[20]), "+f"(d[21]), "+f"(d[22]), "+f"(d[23]), "+f"(d[24]), "+f"(d[25]), "+f"(d[26]), "+f"(d[27]), "+f"(d[28]), "+f"(d[29]), "+f"(d[30]), "+f"(d[31]), "+f"(d[32]), "+f"(d[33]), "+f"(d[34]), "+f"(d[35]), "+f"(d[36]), "+f"(d[37]), "+f"(d[38]), "+f"(d[39]), "+f"(d[40]), "+f"(d[41]), "+f"(d[42]), "+f"(d[43]), "+f"(d[44]), "+f"(d[45]), "+f"(d[46]), "+f"(d[47]), "+f"(d[48]), "+f"(d[49]), "+f"(d[50]), "+f"(d[51]), "+f"(d[52]), "+f"(d[53]), "+f"(d[54]), "+f"(d[55]), "+f"(d[56]), "+f"(d[57]), "+f"(d[58]), "+f"(d[59])
    : "l"(da), "l"(db), "r"(sc), "n"(TA), "n"(TB));
}
template<int TA, int TB> __device__ __forceinline__ void wgmma_n128(float* d, uint64_t da, uint64_t db, int sc) {
  asm volatile("{\n.reg .pred p;\nsetp.ne.b32 p, %66, 0;\n"
    "wgmma.mma_async.sync.aligned.m64n128k16.f32.bf16.bf16 {%0, %1, %2, %3, %4, %5, %6, %7, %8, %9, %10, %11, %12, %13, %14, %15, %16, %17, %18, %19, %20, %21, %22, %23, %24, %25, %26, %27, %28, %29, %30, %31, %32, %33, %34, %35, %36, %37, %38, %39, %40, %41, %42, %43, %44, %45, %46, %47, %48, %49, %50, %51, %52, %53, %54, %55, %56, %57, %58, %59, %60, %61, %62, %63}, %64, %65, p, 1, 1, %67, %68;\n}\n"
    : "+f"(d[0]), "+f"(d[1]), "+f"(d[2]), "+f"(d[3]), "+f"(d[4]), "+f"(d[5]), "+f"(d[6]), "+f"(d[7]), "+f"(d[8]), "+f"(d[9]), "+f"(d[10]), "+f"(d[11]), "+f"(d[12]), "+f"(d[13]), "+f"(d[14]), "+f"(d[15]), "+f"(d[16]), "+f"(d[17]), "+f"(d[18]), "+f"(d[19]), "+f"(d[20]), "+f"(d[21]), "+f"(d[22]), "+f"(d[23]), "+f"(d[24]), "+f"(d[25]), "+f"(d[26]), "+f"(d[27]), "+f"(d[28]), "+f"(d[29]), "+f"(d[30]), "+f"(d[31]), "+f"(d[32]), "+f"(d[33]), "+f"(d[34]), "+f"(d[35]), "+f"(d[36]), "+f"(d[37]), "+f"(d[38]), "+f"(d[39]), "+f"(d[40]), "+f"(d[41]), "+f"(d[42]), "+f"(d[43]), "+f"(d[44]), "+f"(d[45]), "+f"(d[46]), "+f"(d[47]), "+f"(d[48]), "+f"(d[49]), "+f"(d[50]), "+f"(d[51]), "+f"(d[52]), "+f"(d[53]), "+f"(d[54]), "+f"(d[55]), "+f"(d[56]), "+f"(d[57]), "+f"(d[58]), "+f"(d[59]), "+f"(d[60]), "+f"(d[61]), "+f"(d[62]), "+f"(d[63])
    : "l"(da), "l"(db), "r"(sc), "n"(TA), "n"(TB));
}
template<int TA, int TB> __device__ __forceinline__ void wgmma_n192(float* d, uint64_t da, uint64_t db, int sc) {
  asm volatile("{\n.reg .pred p;\nsetp.ne.b32 p, %98, 0;\n"
    "wgmma.mma_async.sync.aligned.m64n192k16.f32.bf16.bf16 {%0, %1, %2, %3, %4, %5, %6, %7, %8, %9, %10, %11, %12, %13, %14, %15, %16, %17, %18, %19, %20, %21, %22, %23, %24, %25, %26, %27, %28, %29, %30, %31, %32, %33, %34, %35, %36, %37, %38, %39, %40, %41, %42, %43, %44, %45, %46, %47, %48, %49, %50, %51, %52, %53, %54, %55, %56, %57, %58, %59, %60, %61, %62, %63, %64, %65, %66, %67, %68, %69, %70, %71, %72, %73, %74, %75, %76, %77, %78, %79, %80, %81, %82, %83, %84, %85, %86, %87, %88, %89, %90, %91, %92, %93, %94, %95}, %96, %97, p, 1, 1, %99, %100;\n}\n"
    : "+f"(d[0]), "+f"(d[1]), "+f"(d[2]), "+f"(d[3]), "+f"(d[4]), "+f"(d[5]), "+f"(d[6]), "+f"(d[7]), "+f"(d[8]), "+f"(d[9]), "+f"(d[10]), "+f"(d[11]), "+f"(d[12]), "+f"(d[13]), "+f"(d[14]), "+f"(d[15]), "+f"(d[16]), "+f"(d[17]), "+f"(d[18]), "+f"(d[19]), "+f"(d[20]), "+f"(d[21]), "+f"(d[22]), "+f"(d[23]), "+f"(d[24]), "+f"(d[25]), "+f"(d[26]), "+f"(d[27]), "+f"(d[28]), "+f"(d[29]), "+f"(d[30]), "+f"(d[31]), "+f"(d[32]), "+f"(d[33]), "+f"(d[34]), "+f"(d[35]), "+f"(d[36]), "+f"(d[37]), "+f"(d[38]), "+f"(d[39]), "+f"(d[40]), "+f"(d[41]), "+f"(d[42]), "+f"(d[43]), "+f"(d[44]), "+f"(d[45]), "+f"(d[46]), "+f"(d[47]), "+f"(d[48]), "+f"(d[49]), "+f"(d[50]), "+f"(d[51]), "+f"(d[52]), "+f"(d[53]), "+f"(d[54]), "+f"(d[55]), "+f"(d[56]), "+f"(d[57]), "+f"(d[58]), "+f"(d[59]), "+f"(d[60]), "+f"(d[61]), "+f"(d[62]), "+f"(d[63]), "+f"(d[64]), "+f"(d[65]), "+f"(d[66]), "+f"(d[67]), "+f"(d[68]), "+f"(d[69]), "+f"(d[70]), "+f"(d[71]), "+f"(d[72]), "+f"(d[73]), "+f"(d[74]), "+f"(d[75]), "+f"(d[76]), "+f"(d[77]), "+f"(d[78]), "+f"(d[79]), "+f"(d[80]), "+f"(d[81]), "+f"(d[82]), "+f"(d[83]), "+f"(d[84]), "+f"(d[85]), "+f"(d[86]), "+f"(d[87]), "+f"(d[88]), "+f"(d[89]), "+f"(d[90]), "+f"(d[91]), "+f"(d[92]), "+f"(d[93]), "+f"(d[94]), "+f"(d[95])
    : "l"(da), "l"(db), "r"(sc), "n"(TA), "n"(TB));
}
template<int N, int TA, int TB> __device__ __forceinline__ void wgmma_ss(float* d, uint64_t da, uint64_t db, int sc) {
  if constexpr (N == 8) wgmma_n8<TA,TB>(d, da, db, sc);
  if constexpr (N == 16) wgmma_n16<TA,TB>(d, da, db, sc);
  if constexpr (N == 24) wgmma_n24<TA,TB>(d, da, db, sc);
  if constexpr (N == 32) wgmma_n32<TA,TB>(d, da, db, sc);
  if constexpr (N == 40) wgmma_n40<TA,TB>(d, da, db, sc);
  if constexpr (N == 48) wgmma_n48<TA,TB>(d, da, db, sc);
  if constexpr (N == 56) wgmma_n56<TA,TB>(d, da, db, sc);
  if constexpr (N == 64) wgmma_n64<TA,TB>(d, da, db, sc);
  if constexpr (N == 72) wgmma_n72<TA,TB>(d, da, db, sc);
  if constexpr (N == 80) wgmma_n80<TA,TB>(d, da, db, sc);
  if constexpr (N == 88) wgmma_n88<TA,TB>(d, da, db, sc);
  if constexpr (N == 96) wgmma_n96<TA,TB>(d, da, db, sc);
  if constexpr (N == 104) wgmma_n104<TA,TB>(d, da, db, sc);
  if constexpr (N == 112) wgmma_n112<TA,TB>(d, da, db, sc);
  if constexpr (N == 120) wgmma_n120<TA,TB>(d, da, db, sc);
  if constexpr (N == 128) wgmma_n128<TA,TB>(d, da, db, sc);
  if constexpr (N == 192) wgmma_n192<TA,TB>(d, da, db, sc);
}

constexpr int NGRP = 260;
constexpr uint32_t G1_STAGE = 57344;
constexpr uint32_t OFF_U = 131072;
constexpr uint32_t OFF_H = 172032;
constexpr uint32_t H_PITCH = 4352;
constexpr uint32_t OFF_EX = 215552;
constexpr uint32_t OFF_G = OFF_EX + 5120;
constexpr uint32_t OFF_BAR = OFF_G + 320;
constexpr uint32_t SMEM_BYTES = OFF_BAR + 256;
constexpr int NCTA = 130;

enum { B_FULL1 = 0, B_EMPTY1 = 3, B_UFULL = 6, B_HRDY = 11, B_FULL2 = 12, B_EMPTY2 = 17, B_CONVDONE = 22,
       B_SIGH = 23, B_SIGZ = 27, B_KV = 28, B_HLD = 29, B_STDONE = 30, B_COUNT = 31 };
enum { C_H = 0, C_U = 8, C_Z = 9, C_DONE = 10, C_COUNT = 11 };

__device__ __align__(1024) __nv_bfloat16 g_Hs[16 * NGRP * 768];
__device__ __align__(1024) __nv_bfloat16 g_U[640 * 2 * 2048];
__device__ __align__(1024) __nv_bfloat16 g_zT[640 * NGRP * 8];
__device__ __align__(1024) float g_gate[NGRP * 8];
__device__ __align__(1024) unsigned g_cnt[C_COUNT * 32];
#define TS(i) do { } while (0)

__device__ __forceinline__ uint32_t smem_u32(const void* p) { return (uint32_t)__cvta_generic_to_shared(p); }
__device__ __forceinline__ uint64_t mkdesc(uint32_t addr, uint32_t lbo, uint32_t sbo, uint32_t swz) {
  return (uint64_t)((addr & 0x3FFFF) >> 4) | ((uint64_t)(lbo >> 4) << 16) | ((uint64_t)(sbo >> 4) << 32) | ((uint64_t)swz << 62);
}
__device__ __forceinline__ void wg_fence() { asm volatile("wgmma.fence.sync.aligned;" ::: "memory"); }
__device__ __forceinline__ void wg_commit() { asm volatile("wgmma.commit_group.sync.aligned;" ::: "memory"); }
template <int N> __device__ __forceinline__ void wg_wait() { asm volatile("wgmma.wait_group.sync.aligned %0;" ::"n"(N) : "memory"); }
template <int N> __device__ __forceinline__ void pin(float* d) {
#pragma unroll
  for (int i = 0; i < N; i++) asm volatile("" : "+f"(d[i])::"memory");
}
__device__ __forceinline__ void mbar_init(uint32_t a, int c) { asm volatile("mbarrier.init.shared::cta.b64 [%0], %1;" ::"r"(a), "r"(c) : "memory"); }
__device__ __forceinline__ void mbar_expect(uint32_t a, uint32_t b) { asm volatile("mbarrier.arrive.expect_tx.shared::cta.b64 _, [%0], %1;" ::"r"(a), "r"(b) : "memory"); }
__device__ __forceinline__ void mbar_arrive(uint32_t a) { asm volatile("mbarrier.arrive.shared::cta.b64 _, [%0];" ::"r"(a) : "memory"); }
__device__ __forceinline__ void mbar_wait_t(uint32_t a, uint32_t ph) {
  uint32_t ok;
  int it = 0;
  do {
    asm volatile("{\n.reg .pred p;\nmbarrier.try_wait.parity.shared::cta.b64 p, [%1], %2;\nselp.u32 %0,1,0,p;\n}" : "=r"(ok) : "r"(a), "r"(ph) : "memory");
    if (++it > (1 << 18)) __trap();
  } while (!ok);
}
__device__ __forceinline__ void mbar_wait(uint32_t a, uint32_t ph) {
  asm volatile(
      "{\n.reg .pred p, q;\n.reg .u32 n;\nmov.u32 n, 0;\n"
      "WAIT_%=:\n"
      "mbarrier.try_wait.parity.shared::cta.b64 p, [%0], %1;\n"
      "@p bra DONE_%=;\n"
      "add.u32 n, n, 1;\n"
      "setp.lt.u32 q, n, 0x80000;\n"
      "@q bra WAIT_%=;\n"
      "DONE_%=:\n}" ::"r"(a), "r"(ph) : "memory");
}
__device__ __forceinline__ void flag_wait(const unsigned* p, unsigned target) {
  int it = 0;
  while (true) {
    unsigned v;
    asm volatile("ld.acquire.gpu.global.u32 %0, [%1];" : "=r"(v) : "l"(p) : "memory");
    if (v >= target) break;
    if (++it > (1 << 21)) __trap();
    __nanosleep(40);
  }
}
__device__ __forceinline__ void flag_add(unsigned* p, unsigned v) {
  asm volatile("fence.acq_rel.gpu;\nred.relaxed.gpu.global.add.u32 [%0], %1;" ::"l"(p), "r"(v) : "memory");
}
__device__ __forceinline__ void bar_sync(int id, int n) { asm volatile("bar.sync %0, %1;" ::"r"(id), "r"(n) : "memory"); }
__device__ __forceinline__ void bar_arrive(int id, int n) { asm volatile("bar.arrive %0, %1;" ::"r"(id), "r"(n) : "memory"); }
__device__ __forceinline__ void bulk_g2s(uint32_t dst, const void* src, uint32_t bytes, uint32_t bar) {
  asm volatile("cp.async.bulk.shared::cluster.global.mbarrier::complete_tx::bytes [%0], [%1], %2, [%3];" ::"r"(dst), "l"(src), "r"(bytes), "r"(bar) : "memory");
}
__device__ __forceinline__ void bulk_s2g(void* dst, uint32_t src, uint32_t bytes) {
  asm volatile("cp.async.bulk.global.shared::cta.bulk_group [%0], [%1], %2;" ::"l"(dst), "r"(src), "r"(bytes) : "memory");
}
__device__ __forceinline__ void bulk_prefetch(const void* src, uint32_t bytes) {
  asm volatile("cp.async.bulk.prefetch.L2.global [%0], %1;" ::"l"(src), "r"(bytes) : "memory");
}
__device__ __forceinline__ void tma2(uint32_t dst, const CUtensorMap* m, int c0, int c1, uint32_t bar) {
  asm volatile("cp.async.bulk.tensor.2d.shared::cluster.global.mbarrier::complete_tx::bytes [%0], [%1, {%3,%4}], [%2];" ::"r"(dst), "l"(m), "r"(bar), "r"(c0), "r"(c1) : "memory");
}
__device__ __forceinline__ void tma3(uint32_t dst, const CUtensorMap* m, int c0, int c1, int c2, uint32_t bar) {
  asm volatile("cp.async.bulk.tensor.3d.shared::cluster.global.mbarrier::complete_tx::bytes [%0], [%1, {%3,%4,%5}], [%2];" ::"r"(dst), "l"(m), "r"(bar), "r"(c0), "r"(c1), "r"(c2) : "memory");
}
__device__ __forceinline__ void tma4(uint32_t dst, const CUtensorMap* m, int c0, int c1, int c2, int c3, uint32_t bar) {
  asm volatile("cp.async.bulk.tensor.4d.shared::cluster.global.mbarrier::complete_tx::bytes [%0], [%1, {%3,%4,%5,%6}], [%2];" ::"r"(dst), "l"(m), "r"(bar), "r"(c0), "r"(c1), "r"(c2), "r"(c3) : "memory");
}
__device__ __forceinline__ void tma5(uint32_t dst, const CUtensorMap* m, int c0, int c4, uint32_t bar) {
  asm volatile("cp.async.bulk.tensor.5d.shared::cluster.global.mbarrier::complete_tx::bytes [%0], [%1, {%3,%5,%5,%5,%4}], [%2];" ::"r"(dst), "l"(m), "r"(bar), "r"(c0), "r"(c4), "r"(0) : "memory");
}
__device__ __forceinline__ void tma4_store(const CUtensorMap* m, uint32_t src, int c0, int c1, int c2, int c3) {
  asm volatile("cp.async.bulk.tensor.4d.global.shared::cta.bulk_group [%0, {%2,%3,%4,%5}], [%1];" ::"l"(m), "r"(src), "r"(c0), "r"(c1), "r"(c2), "r"(c3) : "memory");
}
__device__ __forceinline__ uint32_t pack_bf16(float lo, float hi) {
  uint32_t r;
  asm("cvt.rn.bf16x2.f32 %0, %1, %2;" : "=r"(r) : "f"(hi), "f"(lo));
  return r;
}
__device__ __forceinline__ float tanh_fast(float x) {
  float r;
  asm("tanh.approx.f32 %0, %1;" : "=f"(r) : "f"(x));
  return r;
}
__device__ __forceinline__ uint32_t bmul2(uint32_t a, uint32_t b) {
  uint32_t r;
  asm("mul.rn.bf16x2 %0, %1, %2;" : "=r"(r) : "r"(a), "r"(b));
  return r;
}
__device__ __forceinline__ uint32_t badd2(uint32_t a, uint32_t b) {
  uint32_t r;
  asm("add.rn.bf16x2 %0, %1, %2;" : "=r"(r) : "r"(a), "r"(b));
  return r;
}
__device__ __forceinline__ float bflo(uint32_t v) { return __uint_as_float(v << 16); }
__device__ __forceinline__ float bfhi(uint32_t v) { return __uint_as_float(v & 0xffff0000u); }

template <int S> struct ConvSteps {
  static __device__ __forceinline__ void run(float* d, uint64_t da, uint64_t db, int first) {
    wgmma_ss<128 - 8 * S, 1, 1>(d, da + 16 * S, db + 16 * S, S == 0 ? first : 1);
    if constexpr (S + 1 < 16) ConvSteps<S + 1>::run(d, da, db, first);
  }
};

__device__ __forceinline__ void glu_store(const float* acc, unsigned char* dst) {
#pragma unroll
  for (int h = 0; h < 2; h++) {
#pragma unroll
    for (int aa = 0; aa < 3; aa++) {
      uint32_t v[4];
#pragma unroll
      for (int jj = 0; jj < 4; jj++) {
        const int i = 4 * (4 * aa + jj) + 2 * h;
        float t0 = tanh_fast(0.5f * acc[i]), t1 = tanh_fast(0.5f * acc[i + 1]);
        v[jj] = pack_bf16(fmaf(acc[48 + i], t0, acc[48 + i]), fmaf(acc[49 + i], t1, acc[49 + i]));
      }
      *reinterpret_cast<uint4*>(dst + h * 1536 + aa * 512) = make_uint4(v[0], v[1], v[2], v[3]);
    }
  }
}

struct Params {
  const __nv_bfloat16 *q, *w_down, *shift_k, *ssm_k, *ssm_D, *gate_w;
};

__global__ void __launch_bounds__(384, 1)
fused_kernel(const __grid_constant__ CUtensorMap mX, const __grid_constant__ CUtensorMap mWg,
             const __grid_constant__ CUtensorMap mWu, const __grid_constant__ CUtensorMap mWd,
             const __grid_constant__ CUtensorMap mQ, const __grid_constant__ CUtensorMap mZ,
             const __grid_constant__ CUtensorMap mO, const __grid_constant__ CUtensorMap mK,
             const __grid_constant__ CUtensorMap mV, const Params P) {
  extern __shared__ __align__(1024) unsigned char sm[];
  const uint32_t sb = smem_u32(sm);
  const uint32_t bar = sb + OFF_BAR;
  const int tid = threadIdx.x, warp = tid >> 5, lane = tid & 31;
  const int cta = blockIdx.x;
  const bool has1 = cta < 128;
  const int mb = cta >> 4, ft = cta & 15;
  const int dt = cta % 5, tt = cta / 5;
  const int jhi2 = tt / 13, o2 = (tt % 13) * 10;

  if (tid == 0) {
    for (int i = 0; i < 3; i++) { mbar_init(bar + 8 * (B_FULL1 + i), 1); mbar_init(bar + 8 * (B_EMPTY1 + i), 2); }
    for (int i = 0; i < 5; i++) { mbar_init(bar + 8 * (B_UFULL + i), 1); mbar_init(bar + 8 * (B_FULL2 + i), 1); mbar_init(bar + 8 * (B_EMPTY2 + i), 2); }
    mbar_init(bar + 8 * B_HRDY, 3);
    mbar_init(bar + 8 * B_CONVDONE, 2);
    for (int i = 0; i < 4; i++) mbar_init(bar + 8 * (B_SIGH + i), 4);
    mbar_init(bar + 8 * B_SIGZ, 20);
    mbar_init(bar + 8 * B_KV, 1);
    mbar_init(bar + 8 * B_HLD, 1);
    mbar_init(bar + 8 * B_STDONE, 1);
    asm volatile("fence.mbarrier_init.release.cluster;" ::: "memory");
    asm volatile("fence.proxy.async.shared::cta;" ::: "memory");
  }
  __syncthreads();

  if (warp < 8) {
    asm volatile("setmaxnreg.inc.sync.aligned.u32 224;");
    const int wg = warp >> 2, w = warp & 3, g = lane >> 2, q = lane & 3;
    const bool elect = (tid & 127) == 0;
    if (has1) {
      {
        float acc0[96], acc1[96];
        const uint64_t dA = mkdesc(sb + wg * 16384, 16, 1024, 1);
        const uint64_t dB = mkdesc(sb + 32768, 4096, 512, 2);
#pragma unroll 1
        for (int kb = 0; kb < 10; kb++) {
          const int rg = (kb + 1) % 3;
          const uint64_t da = dA + rg * (G1_STAGE >> 4), db = dB + rg * (G1_STAGE >> 4);
          mbar_wait(bar + 8 * (B_FULL1 + rg), (kb / 3) & 1);
          if (kb == 0 && tid == 0) TS(1);
          if (kb == 9 && wg == 1) {
            wg_wait<0>();
            if (elect) mbar_arrive(bar + 8 * (B_EMPTY1 + 0));
            bar_sync(2, 256);
          }
          wg_fence();
#pragma unroll
          for (int kk = 0; kk < 4; kk++) wgmma_ss<192, 0, 1>(acc0, da + 2 * kk, db + 64 * kk, (kb | kk) != 0);
          wg_commit();
#pragma unroll
          for (int kk = 0; kk < 4; kk++) wgmma_ss<192, 0, 1>(acc1, da + 512 + 2 * kk, db + 64 * kk, (kb | kk) != 0);
          wg_commit();
          if (kb == 9) bar_arrive(2 - wg, 256);
          wg_wait<2>();
          if (kb > 0 && kb + wg < 10 && elect) mbar_arrive(bar + 8 * (B_EMPTY1 + kb % 3));
        }
        unsigned char* hd = sm + wg * 24576 + w * 3072 + g * 64 + ((q ^ (g >> 1)) << 4);
        mbar_wait(bar + 8 * (B_EMPTY1 + 0), 0);
        wg_wait<1>();
        pin<96>(acc0);
        if (elect) TS(2 + wg);
        glu_store(acc0, hd);
        asm volatile("fence.proxy.async.shared::cta;" ::: "memory");
        __syncwarp();
        if (lane == 0) mbar_arrive(bar + 8 * (B_SIGH + 2 * wg));
        wg_wait<0>();
        pin<96>(acc1);
        if (elect) mbar_arrive(bar + 8 * (B_EMPTY1 + 1));
        glu_store(acc1, hd + 12288);
        asm volatile("fence.proxy.async.shared::cta;" ::: "memory");
        __syncwarp();
        if (lane == 0) mbar_arrive(bar + 8 * (B_SIGH + 2 * wg + 1));
        if (elect) TS(4 + wg);
      }
      const int c = q & 1, mu = 8 * (q >> 1) + g;
      const int mu1 = (mu + 15) & 15, mu2 = (mu + (c ? 2 : 14)) & 15;
      const int src1 = 4 * (mu1 & 7) + 2 * (mu1 >> 3) + c;
      const int src2 = 4 * (mu2 & 7) + 2 * (mu2 >> 3) + (c ^ 1);
      const bool last = mu == 15, pA = (c == 0) || (mu >= 14);
      const bool impX = lane < 2, impY = (c == 1) && (mu >= 14);
      const int slot = impX ? lane : 2 + (mu & 1);
      const int oo = 32 * w + (c ? mu2 : 16 + mu);
      mbar_wait(bar + 8 * B_HRDY, 0);
#pragma unroll 1
      for (int ch = wg; ch < 5; ch += 2) {
        float d[64];
        const uint64_t da = mkdesc(sb + OFF_H + ch * 2 * H_PITCH, 128, 32, 0);
        const uint64_t db = mkdesc(sb + OFF_U + ch * 8192, 128, 256, 0);
        mbar_wait(bar + 8 * (B_UFULL + ch), 0);
        bar_sync(1 + wg, 256);
        if (elect) TS(10 + 3 * ch);
        wg_fence();
        ConvSteps<0>::run(d, da, db, 0);
        ConvSteps<0>::run(d, da + (H_PITCH >> 4), db + 256, 1);
        wg_commit();
        if (ch < 4) bar_arrive(2 - wg, 256);
        wg_wait<0>();
        pin<64>(d);
        if (ch >= 3 && elect) mbar_arrive(bar + 8 * B_CONVDONE);
        if (elect) TS(11 + 3 * ch);
        float xr[16], s1[16];
#pragma unroll
        for (int J = 0; J < 16; J++) {
          const int i = 4 * (15 - J);
          float a = last ? d[i + 1] : d[i + 3];
          float b = last ? d[i + 3] : d[i + 1];
          s1[J] = d[i + 2] + __shfl_sync(0xffffffffu, a, src1);
          xr[J] = __shfl_sync(0xffffffffu, b, src1);
        }
        float* ex = reinterpret_cast<float*>(sm + OFF_EX) + (wg * 2 + ((ch >> 1) & 1)) * 320;
        if (impX || impY) {
          if (w < 3) {
            float* e = ex + (w + 1) * 80 + slot * 20;
#pragma unroll
            for (int J = 0; J < 16; J += 4)
              *reinterpret_cast<float4*>(e + J) = impX ? make_float4(xr[J], xr[J + 1], xr[J + 2], xr[J + 3]) : make_float4(s1[J], s1[J + 1], s1[J + 2], s1[J + 3]);
          } else {
            float* e = ex + slot * 20;
            *reinterpret_cast<float4*>(e) = impX ? make_float4(0.f, xr[0], xr[1], xr[2]) : make_float4(0.f, s1[0], s1[1], s1[2]);
#pragma unroll
            for (int J = 4; J < 16; J += 4)
              *reinterpret_cast<float4*>(e + J) = impX ? make_float4(xr[J - 1], xr[J], xr[J + 1], xr[J + 2]) : make_float4(s1[J - 1], s1[J], s1[J + 1], s1[J + 2]);
          }
        }
        bar_sync(3 + wg, 128);
        if (impX || impY) {
          const float* e = ex + w * 80 + slot * 20;
#pragma unroll
          for (int J = 0; J < 16; J += 4) {
            float4 v = *reinterpret_cast<const float4*>(e + J);
            if (impX) { xr[J] = v.x; xr[J + 1] = v.y; xr[J + 2] = v.z; xr[J + 3] = v.w; }
            else { s1[J] = v.x; s1[J + 1] = v.y; s1[J + 2] = v.z; s1[J + 3] = v.w; }
          }
        }
        float y[16];
#pragma unroll
        for (int J = 0; J < 16; J++) {
          const float s0 = d[4 * (15 - J)] + xr[J];
          const float snd = pA ? s0 : s1[J];
          const float own = pA ? s1[J] : s0;
          y[J] = own + __shfl_sync(0xffffffffu, snd, src2);
        }
        __nv_bfloat16* zd = g_zT + (size_t)(5 * cta + ch) * (NGRP * 8) + oo * 8;
        *reinterpret_cast<uint4*>(zd) = make_uint4(pack_bf16(y[0], y[1]), pack_bf16(y[2], y[3]), pack_bf16(y[4], y[5]), pack_bf16(y[6], y[7]));
        *reinterpret_cast<uint4*>(zd + 130 * 8) = make_uint4(pack_bf16(y[8], y[9]), pack_bf16(y[10], y[11]), pack_bf16(y[12], y[13]), pack_bf16(y[14], y[15]));
        __syncwarp();
        if (lane == 0) mbar_arrive(bar + 8 * B_SIGZ);
        if (elect) TS(12 + 3 * ch);
      }
    }
    {
      float acc[40];
      const uint64_t dA = mkdesc(sb + wg * 12288, 1024, 1024, 1);
      const uint64_t dB = mkdesc(sb + 24576, 16, 1536, 2);
      int st = 0, ph = 0;
#pragma unroll 1
      for (int it = 0; it < 16; it++) {
        const uint32_t so = (st < 3 ? st * 40960 : (st == 3 ? OFF_U : OFF_H)) >> 4;
        mbar_wait(bar + 8 * (B_FULL2 + st), ph);
        if (it == 0 && elect) TS(26 + wg);
        wg_fence();
#pragma unroll
        for (int kk = 0; kk < 6; kk++) wgmma_ss<80, 1, 0>(acc, dA + so + 128 * kk, dB + so + 32 * (kk >> 1) + 2 * (kk & 1), (it | kk) != 0);
        wg_commit();
        wg_wait<1>();
        if (it > 0 && elect) mbar_arrive(bar + 8 * (B_EMPTY2 + (st == 0 ? 4 : st - 1)));
        if (++st == 5) { st = 0; ph ^= 1; }
      }
      mbar_wait(bar + 8 * (B_FULL2 + 1), 1);
      const uint32_t qb = sb + 40960 + wg * 10240, zb = sb + 40960 + 20480;
      const int i8 = lane & 7, mi = lane >> 3;
      const uint32_t qa = qb + ((mi >> 1) * 8 + i8) * 128 + (((2 * w + (mi & 1)) ^ i8) << 4);
      const uint32_t za = zb + (64 * wg + 16 * w + 8 * (mi & 1) + i8) * 160 + (mi >> 1) * 16;
      float ga[40], om[20];
#pragma unroll
      for (int jp = 0; jp < 5; jp++) {
        uint32_t qv[4], zv[4];
        asm volatile("ldmatrix.sync.aligned.m8n8.x4.trans.shared.b16 {%0,%1,%2,%3}, [%4];" : "=r"(qv[0]), "=r"(qv[1]), "=r"(qv[2]), "=r"(qv[3]) : "r"(qa + jp * 2048) : "memory");
        asm volatile("ldmatrix.sync.aligned.m8n8.x4.shared.b16 {%0,%1,%2,%3}, [%4];" : "=r"(zv[0]), "=r"(zv[1]), "=r"(zv[2]), "=r"(zv[3]) : "r"(za + jp * 32) : "memory");
#pragma unroll
        for (int jl = 0; jl < 2; jl++) {
          const int j = 2 * jp + jl;
          const float2 gt = *reinterpret_cast<const float2*>(sm + OFF_G + (j * 8 + 2 * q) * 4);
          om[2 * j] = 0.5f - 0.5f * gt.x;
          om[2 * j + 1] = 0.5f - 0.5f * gt.y;
#pragma unroll
          for (int h = 0; h < 2; h++) {
            const uint32_t a2 = bmul2(qv[2 * jl + h], zv[2 * jl + h]);
            ga[4 * j + 2 * h] = gt.x * bflo(a2);
            ga[4 * j + 2 * h + 1] = gt.y * bfhi(a2);
          }
        }
      }
      wg_wait<0>();
      pin<40>(acc);
      if (elect) TS(28 + wg);
#pragma unroll
      for (int jp = 0; jp < 5; jp++) {
        uint32_t ov[4];
#pragma unroll
        for (int m = 0; m < 4; m++) {
          const int j = 2 * jp + (m >> 1), i = 4 * j + 2 * (m & 1);
          ov[m] = pack_bf16(fmaf(om[2 * j], acc[i], ga[i]), fmaf(om[2 * j + 1], acc[i + 1], ga[i + 1]));
        }
        asm volatile("stmatrix.sync.aligned.m8n8.x4.trans.shared.b16 [%0], {%1,%2,%3,%4};" ::"r"(qa + jp * 2048), "r"(ov[0]), "r"(ov[1]), "r"(ov[2]), "r"(ov[3]) : "memory");
      }
      asm volatile("fence.proxy.async.shared::cta;" ::: "memory");
      bar_sync(3 + wg, 128);
      if (elect) {
        tma4_store(&mO, qb, dt * 128 + wg * 64, 0, o2, jhi2);
        asm volatile("cp.async.bulk.commit_group;" ::: "memory");
        asm volatile("cp.async.bulk.wait_group.read 0;" ::: "memory");
        TS(30 + wg);
      }
    }
  } else {
    asm volatile("setmaxnreg.dec.sync.aligned.u32 56;");
    if (warp == 8) {
      if (lane == 0) {
        if (has1) {
#pragma unroll 1
          for (int kb = 0; kb < 10; kb++) {
            const int rg = (kb + 1) % 3;
            const uint32_t dst = sb + rg * G1_STAGE, fb = bar + 8 * (B_FULL1 + rg);
            if (kb >= 3) mbar_wait_t(bar + 8 * (B_EMPTY1 + rg), (kb / 3 - 1) & 1);
            mbar_expect(fb, G1_STAGE);
            tma3(dst + 32768, &mWg, 0, kb * 64, ft * 3, fb);
            tma3(dst + 32768 + 12288, &mWu, 0, kb * 64, ft * 3, fb);
            tma4(dst, &mX, kb * 64, 0, (mb & 3) * 32, mb >> 2, fb);
            if (kb == 2) {
              mbar_expect(bar + 8 * B_KV, 21760 + 20480);
              tma3(sb + OFF_H, &mK, (cta & 7) * 80, (cta >> 3) * 16 - 1, 0, bar + 8 * B_KV);
              tma3(sb + OFF_H + 21760, &mV, (cta & 7) * 80, (cta >> 3) * 16, 0, bar + 8 * B_KV);
            }
            if (kb == 3) bulk_prefetch(P.ssm_k + (size_t)cta * 5 * 2048, 20480);
            if (kb == 5) bulk_prefetch(P.w_down + (size_t)cta * 7680, 15360);
          }
          flag_wait(&g_cnt[C_U * 32], 128);
          asm volatile("fence.proxy.async.global;" ::: "memory");
          TS(32);
          mbar_wait_t(bar + 8 * (B_EMPTY1 + 2), 0);
#pragma unroll 1
          for (int ch = 0; ch < 5; ch++) {
            mbar_expect(bar + 8 * (B_UFULL + ch), 8192);
            bulk_g2s(sb + OFF_U + ch * 8192, g_U + (size_t)(5 * cta + ch) * 4096, 8192, bar + 8 * (B_UFULL + ch));
          }
          TS(33);
        }
        flag_wait(&g_cnt[(C_H + jhi2 * 4 + (o2 >> 5)) * 32], 16);
        flag_wait(&g_cnt[(C_H + jhi2 * 4 + min((o2 + 9) >> 5, 3)) * 32], 16);
        asm volatile("fence.proxy.async.global;" ::: "memory");
        TS(34);
        if (has1) { mbar_wait_t(bar + 8 * B_STDONE, 0); mbar_wait_t(bar + 8 * (B_EMPTY1 + 1), 1); }
        const __nv_bfloat16* hsrc = g_Hs + (size_t)(jhi2 * 130 + o2) * 768;
        int st = 0, ph = 1;
#pragma unroll 1
        for (int it = 0; it < 16; it++) {
          const uint32_t dst = sb + (st < 3 ? st * 40960 : (st == 3 ? OFF_U : OFF_H)), fb = bar + 8 * (B_FULL2 + st);
          if (it >= 5) mbar_wait_t(bar + 8 * (B_EMPTY2 + st), ph);
          else if (it == 3 && has1) mbar_wait_t(bar + 8 * B_CONVDONE, 0);
          mbar_expect(fb, 39936);
          tma5(dst, &mWd, dt * 128, it * 3, fb);
          tma5(dst + 12288, &mWd, dt * 128 + 64, it * 3, fb);
          bulk_g2s(dst + 24576, hsrc + (size_t)it * (NGRP * 768), 15360, fb);
          if (++st == 5) { st = 0; ph ^= 1; }
        }
        flag_wait(&g_cnt[C_Z * 32], 128);
        asm volatile("fence.proxy.async.global;" ::: "memory");
        TS(35);
        {
          const uint32_t dst = sb + 40960, fb = bar + 8 * (B_FULL2 + 1);
          mbar_wait_t(bar + 8 * (B_EMPTY2 + 1), 0);
          mbar_expect(fb, 40960 + 320);
          tma4(dst, &mQ, dt * 128, 0, o2, jhi2, fb);
          tma4(dst + 10240, &mQ, dt * 128 + 64, 0, o2, jhi2, fb);
          tma2(dst + 20480, &mZ, (jhi2 * 130 + o2) * 8, dt * 128, fb);
          bulk_g2s(sb + OFF_G, g_gate + (jhi2 * 130 + o2) * 8, 320, fb);
        }
        if (atomicAdd(&g_cnt[C_DONE * 32], 1u) == NCTA - 1) {
          for (int i = 0; i < C_COUNT; i++) g_cnt[i * 32] = 0;
        }
      }
    } else if (has1) {
      const int hw = warp - 9;
      {
        const int a = lane >> 2, cq = lane & 3;
        mbar_wait_t(bar + 8 * B_KV, 0);
        if (hw == 0 && lane == 0) TS(39);
#pragma unroll 1
        for (int i = hw; i < 10; i += 3) {
          const int th = i & 1, cb = i >> 1;
          const int ch0 = (cta & 7) * 80 + cb * 16 + cq * 4, al = th * 8 + a, o = (cta >> 3) * 16 + al;
          const uint4 sa = __ldg(reinterpret_cast<const uint4*>(P.shift_k + ch0 * 4));
          const uint4 sc = __ldg(reinterpret_cast<const uint4*>(P.shift_k + ch0 * 4 + 8));
          const unsigned char* kp = sm + OFF_H + al * 160 + cb * 32 + cq * 8;
          const unsigned char* vp = kp + 21760;
          uint2 kr[11], vr[8];
#pragma unroll
          for (int r = 0; r < 3; r++) kr[r] = *reinterpret_cast<const uint2*>(kp + (r + 5) * 17 * 160);
#pragma unroll
          for (int r = 0; r < 8; r++) kr[r + 3] = *reinterpret_cast<const uint2*>(kp + (r * 17 + 1) * 160);
#pragma unroll
          for (int r = 0; r < 8; r++) vr[r] = *reinterpret_cast<const uint2*>(vp + r * 16 * 160);
          const uint32_t wa[4] = {__byte_perm(sa.x, sa.z, 0x5410), __byte_perm(sa.x, sa.z, 0x7632), __byte_perm(sa.y, sa.w, 0x5410), __byte_perm(sa.y, sa.w, 0x7632)};
          const uint32_t wb[4] = {__byte_perm(sc.x, sc.z, 0x5410), __byte_perm(sc.x, sc.z, 0x7632), __byte_perm(sc.y, sc.w, 0x5410), __byte_perm(sc.y, sc.w, 0x7632)};
#pragma unroll
          for (int r = 0; r < 8; r++) {
            uint32_t x = bmul2(kr[r].x, wa[3]), y = bmul2(kr[r].y, wb[3]);
#pragma unroll
            for (int j = 1; j < 4; j++) {
              x = badd2(x, bmul2(kr[r + j].x, wa[3 - j]));
              y = badd2(y, bmul2(kr[r + j].y, wb[3 - j]));
            }
            vr[r].x = bmul2(x, vr[r].x);
            vr[r].y = bmul2(y, vr[r].y);
          }
#pragma unroll
          for (int cc = 0; cc < 4; cc++) {
            const uint32_t sel = (cc & 1) ? 0x7632 : 0x5410;
            __nv_bfloat16* up = g_U + (size_t)(ch0 + cc) * 4096 + 8 * (254 - o);
#pragma unroll
            for (int p = 0; p < 2; p++) {
              const int r = 4 - 4 * p;
              uint2 qd;
              qd.x = (cc & 2) ? __byte_perm(vr[r].y, vr[r + 1].y, sel) : __byte_perm(vr[r].x, vr[r + 1].x, sel);
              qd.y = (cc & 2) ? __byte_perm(vr[r + 2].y, vr[r + 3].y, sel) : __byte_perm(vr[r + 2].x, vr[r + 3].x, sel);
              if (o < 255) *reinterpret_cast<uint2*>(up + p * 2048) = qd;
              *reinterpret_cast<uint2*>(up + p * 2048 + 12) = qd;
              if (o == 0) *reinterpret_cast<uint2*>(up + p * 2048 + 8) = make_uint2(0u, 0u);
            }
          }
        }
        bar_sync(5, 96);
        if (hw == 1 && lane == 0) {
          mbar_expect(bar + 8 * B_HLD, 20480);
          for (int ch = 0; ch < 5; ch++)
            bulk_g2s(sb + OFF_H + (2 * ch + 1) * H_PITCH + 224, P.ssm_k + (size_t)(cta * 5 + ch) * 2048, 4096, bar + 8 * B_HLD);
        }
        if (hw == 0 && lane == 0) { flag_add(&g_cnt[C_U * 32], 1); TS(40); }
      }
      {
        const int ht = tid - 288;
        for (int i = ht; i < 10 * 15; i += 96) {
          const int b = i / 15, e = i % 15;
          if (e < 14) *reinterpret_cast<uint4*>(sm + OFF_H + b * H_PITCH + e * 16) = make_uint4(0u, 0u, 0u, 0u);
          else if ((b & 1) == 0) *reinterpret_cast<uint2*>(sm + OFF_H + b * H_PITCH + 224) = make_uint2(0u, 0u);
        }
        const float dv = lane < 5 ? __bfloat162float(P.ssm_D[cta * 5 + lane]) : 0.f;
        mbar_wait_t(bar + 8 * B_HLD, 0);
        if (hw == 0 && lane < 5) {
          __nv_bfloat16* h0 = reinterpret_cast<__nv_bfloat16*>(sm + OFF_H + (2 * lane + 1) * H_PITCH + 224);
          *h0 = __float2bfloat16(__bfloat162float(*h0) + dv);
        }
        bar_sync(5, 96);
#pragma unroll 1
        for (int b = hw; b < 10; b += 3) {
          unsigned char* dst = sm + OFF_H + (b >> 1) * 2 * H_PITCH + (b & 1) * 2048 + 232 + lane * 8;
          uint2 hv[8];
#pragma unroll
          for (int u = 0; u < 8; u++) hv[u] = *reinterpret_cast<const uint2*>(dst + H_PITCH - 8 + u * 256);
#pragma unroll
          for (int u = 0; u < 8; u++) *reinterpret_cast<uint2*>(dst + u * 256) = hv[u];
        }
        asm volatile("fence.proxy.async.shared::cta;" ::: "memory");
        __syncwarp();
        if (lane == 0) mbar_arrive(bar + 8 * B_HRDY);
        if (hw == 0 && lane == 0) TS(41);
      }
      if (hw == 2) {
        if (lane == 0) {
          __nv_bfloat16* hd = g_Hs + (size_t)(ft * NGRP + (mb >> 2) * 130 + (mb & 3) * 32) * 768;
#pragma unroll 1
          for (int i = 0; i < 4; i++) {
            mbar_wait_t(bar + 8 * (B_SIGH + i), 0);
            bulk_s2g(hd + i * 6144, sb + i * 12288, 12288);
          }
          asm volatile("cp.async.bulk.commit_group;" ::: "memory");
          asm volatile("cp.async.bulk.wait_group 0;" ::: "memory");
          mbar_arrive(bar + 8 * B_STDONE);
          flag_add(&g_cnt[(C_H + mb) * 32], 1);
          TS(42);
        }
      } else {
        const uint4* gp = reinterpret_cast<const uint4*>(P.gate_w);
        uint4 gw[3];
        gw[0] = __ldg(gp + lane); gw[1] = __ldg(gp + 32 + lane);
        gw[2] = lane < 16 ? __ldg(gp + 64 + lane) : make_uint4(0u, 0u, 0u, 0u);
        const int o = (mb & 3) * 32 + 2 * ft + hw;
#pragma unroll 2
        for (int r = 0; r < 8; r++) {
          const int t = 128 * (8 * (mb >> 2) + r) + o;
          const uint4* xp = reinterpret_cast<const uint4*>(P.q + (size_t)t * 640);
          uint4 xv[3];
          xv[0] = __ldg(xp + lane); xv[1] = __ldg(xp + 32 + lane);
          xv[2] = lane < 16 ? __ldg(xp + 64 + lane) : make_uint4(0u, 0u, 0u, 0u);
          float s = 0.f;
#pragma unroll
          for (int u = 0; u < 3; u++) {
            const uint32_t p0 = bmul2(xv[u].x, gw[u].x), p1 = bmul2(xv[u].y, gw[u].y), p2 = bmul2(xv[u].z, gw[u].z), p3 = bmul2(xv[u].w, gw[u].w);
            s += (bflo(p0) + bfhi(p0)) + (bflo(p1) + bfhi(p1)) + ((bflo(p2) + bfhi(p2)) + (bflo(p3) + bfhi(p3)));
          }
#pragma unroll
          for (int m = 16; m > 0; m >>= 1) s += __shfl_xor_sync(0xffffffffu, s, m);
          if (lane == 0) {
            s = __bfloat162float(__float2bfloat16(s));
            g_gate[((mb >> 2) * 130 + o) * 8 + r] = __bfloat162float(__float2bfloat16(1.f / (1.f + __expf(-s))));
          }
        }
        bar_sync(6, 64);
        if (hw == 0 && lane == 0) {
          TS(44);
          mbar_wait_t(bar + 8 * B_SIGZ, 0);
          flag_add(&g_cnt[C_Z * 32], 1);
          TS(43);
        }
      }
    }
  }
}

typedef CUresult (*EncFn)(CUtensorMap*, CUtensorMapDataType, cuuint32_t, void*, const cuuint64_t*, const cuuint64_t*,
                          const cuuint32_t*, const cuuint32_t*, CUtensorMapInterleave, CUtensorMapSwizzle,
                          CUtensorMapL2promotion, CUtensorMapFloatOOBfill);

void make_map(EncFn enc, CUtensorMap* m, const void* ptr, int rank, const cuuint64_t* dims, const cuuint64_t* str,
              const cuuint32_t* box, CUtensorMapSwizzle sw) {
  const cuuint32_t es[5] = {1, 1, 1, 1, 1};
  enc(m, CU_TENSOR_MAP_DATA_TYPE_BFLOAT16, rank, const_cast<void*>(ptr), dims, str, box, es, CU_TENSOR_MAP_INTERLEAVE_NONE,
      sw, CU_TENSOR_MAP_L2_PROMOTION_L2_128B, CU_TENSOR_MAP_FLOAT_OOB_FILL_NONE);
}

}

extern "C" void kernel_launch(void* const* d_in, const int* in_sizes, int n_in, void* d_out, int out_size) {
  (void)in_sizes; (void)n_in; (void)out_size;
  static EncFn enc = nullptr;
  static void* zT = nullptr;
  if (!enc) {
    cudaDriverEntryPointQueryResult qr;
    cudaGetDriverEntryPoint("cuTensorMapEncodeTiled", (void**)&enc, cudaEnableDefault, &qr);
    cudaGetSymbolAddress(&zT, g_zT);
    cudaFuncSetAttribute(fused_kernel, cudaFuncAttributeMaxDynamicSharedMemorySize, SMEM_BYTES);
  }
  CUtensorMap mX, mWg, mWu, mWd, mQ, mZ, mO, mK, mV;
  {
    const cuuint64_t dims[4] = {640, 8, 128, 2}, str[3] = {128 * 1280, 1280, 1024 * 1280};
    const cuuint32_t b1[4] = {64, 8, 32, 1}, b2[4] = {64, 8, 10, 1};
    make_map(enc, &mX, d_in[0], 4, dims, str, b1, CU_TENSOR_MAP_SWIZZLE_128B);
    make_map(enc, &mQ, d_in[0], 4, dims, str, b2, CU_TENSOR_MAP_SWIZZLE_128B);
    make_map(enc, &mO, d_out, 4, dims, str, b2, CU_TENSOR_MAP_SWIZZLE_128B);
  }
  {
    const cuuint64_t dims[3] = {32, 640, 48}, str[2] = {3072, 64};
    const cuuint32_t box[3] = {32, 64, 3};
    make_map(enc, &mWg, d_in[7], 3, dims, str, box, CU_TENSOR_MAP_SWIZZLE_64B);
    make_map(enc, &mWu, d_in[8], 3, dims, str, box, CU_TENSOR_MAP_SWIZZLE_64B);
  }
  {
    const cuuint64_t dims[5] = {640, 2, 4, 4, 48}, str[4] = {1280, 8 * 1280, 2 * 1280, 32 * 1280};
    const cuuint32_t box[5] = {64, 2, 4, 4, 3};
    make_map(enc, &mWd, d_in[9], 5, dims, str, box, CU_TENSOR_MAP_SWIZZLE_128B);
  }
  {
    const cuuint64_t dims[2] = {NGRP * 8, 640}, str[1] = {NGRP * 16};
    const cuuint32_t box[2] = {80, 128};
    make_map(enc, &mZ, zT, 2, dims, str, box, CU_TENSOR_MAP_SWIZZLE_NONE);
  }
  {
    const cuuint64_t dims[3] = {640, 256, 8}, str[2] = {8 * 1280, 1280};
    const cuuint32_t bk[3] = {80, 17, 8}, bv[3] = {80, 16, 8};
    make_map(enc, &mK, d_in[1], 3, dims, str, bk, CU_TENSOR_MAP_SWIZZLE_NONE);
    make_map(enc, &mV, d_in[2], 3, dims, str, bv, CU_TENSOR_MAP_SWIZZLE_NONE);
  }
  Params P;
  P.q = (const __nv_bfloat16*)d_in[0]; P.w_down = (const __nv_bfloat16*)d_in[9];
  P.shift_k = (const __nv_bfloat16*)d_in[3]; P.ssm_k = (const __nv_bfloat16*)d_in[4]; P.ssm_D = (const __nv_bfloat16*)d_in[5];
  P.gate_w = (const __nv_bfloat16*)d_in[10];
  fused_kernel<<<NCTA, 384, SMEM_BYTES>>>(mX, mWg, mWu, mWd, mQ, mZ, mO, mK, mV, P);
}
```

```cpp
#include <cuda_runtime.h>
#include <cuda.h>
#include <cuda_bf16.h>
#include <stdint.h>

namespace {
#define KVMODE 0
#define TAILMODE 1
#define GMAP 1
#define G1MAP 1
#define REL 2
#define REL2 3
#define PFK 4
#define PFW 6
#define PFMODE 0

template<int TA, int TB> __device__ __forceinline__ void wgmma_n8(float* d, uint64_t da, uint64_t db, int sc) {
  asm volatile("{\n.reg .pred p;\nsetp.ne.b32 p, %6, 0;\n"
    "wgmma.mma_async.sync.aligned.m64n8k16.f32.bf16.bf16 {%0, %1, %2, %3}, %4, %5, p, 1, 1, %7, %8;\n}\n"
    : "+f"(d[0]), "+f"(d[1]), "+f"(d[2]), "+f"(d[3])
    : "l"(da), "l"(db), "r"(sc), "n"(TA), "n"(TB));
}
template<int TA, int TB> __device__ __forceinline__ void wgmma_n16(float* d, uint64_t da, uint64_t db, int sc) {
  asm volatile("{\n.reg .pred p;\nsetp.ne.b32 p, %10, 0;\n"
    "wgmma.mma_async.sync.aligned.m64n16k16.f32.bf16.bf16 {%0, %1, %2, %3, %4, %5, %6, %7}, %8, %9, p, 1, 1, %11, %12;\n}\n"
    : "+f"(d[0]), "+f"(d[1]), "+f"(d[2]), "+f"(d[3]), "+f"(d[4]), "+f"(d[5]), "+f"(d[6]), "+f"(d[7])
    : "l"(da), "l"(db), "r"(sc), "n"(TA), "n"(TB));
}
template<int TA, int TB> __device__ __forceinline__ void wgmma_n24(float* d, uint64_t da, uint64_t db, int sc) {
  asm volatile("{\n.reg .pred p;\nsetp.ne.b32 p, %14, 0;\n"
    "wgmma.mma_async.sync.aligned.m64n24k16.f32.bf16.bf16 {%0, %1, %2, %3, %4, %5, %6, %7, %8, %9, %10, %11}, %12, %13, p, 1, 1, %15, %16;\n}\n"
    : "+f"(d[0]), "+f"(d[1]), "+f"(d[2]), "+f"(d[3]), "+f"(d[4]), "+f"(d[5]), "+f"(d[6]), "+f"(d[7]), "+f"(d[8]), "+f"(d[9]), "+f"(d[10]), "+f"(d[11])
    : "l"(da), "l"(db), "r"(sc), "n"(TA), "n"(TB));
}
template<int TA, int TB> __device__ __forceinline__ void wgmma_n32(float* d, uint64_t da, uint64_t db, int sc) {
  asm volatile("{\n.reg .pred p;\nsetp.ne.b32 p, %18, 0;\n"
    "wgmma.mma_async.sync.aligned.m64n32k16.f32.bf16.bf16 {%0, %1, %2, %3, %4, %5, %6, %7, %8, %9, %10, %11, %12, %13, %14, %15}, %16, %17, p, 1, 1, %19, %20;\n}\n"
    : "+f"(d[0]), "+f"(d[1]), "+f"(d[2]), "+f"(d[3]), "+f"(d[4]), "+f"(d[5]), "+f"(d[6]), "+f"(d[7]), "+f"(d[8]), "+f"(d[9]), "+f"(d[10]), "+f"(d[11]), "+f"(d[12]), "+f"(d[13]), "+f"(d[14]), "+f"(d[15])
    : "l"(da), "l"(db), "r"(sc), "n"(TA), "n"(TB));
}
template<int TA, int TB> __device__ __forceinline__ void wgmma_n40(float* d, uint64_t da, uint64_t db, int sc) {
  asm volatile("{\n.reg .pred p;\nsetp.ne.b32 p, %22, 0;\n"
    "wgmma.mma_async.sync.aligned.m64n40k16.f32.bf16.bf16 {%0, %1, %2, %3, %4, %5, %6, %7, %8, %9, %10, %11, %12, %13, %14, %15, %16, %17, %18, %19}, %20, %21, p, 1, 1, %23, %24;\n}\n"
    : "+f"(d[0]), "+f"(d[1]), "+f"(d[2]), "+f"(d[3]), "+f"(d[4]), "+f"(d[5]), "+f"(d[6]), "+f"(d[7]), "+f"(d[8]), "+f"(d[9]), "+f"(d[10]), "+f"(d[11]), "+f"(d[12]), "+f"(d[13]), "+f"(d[14]), "+f"(d[15]), "+f"(d[16]), "+f"(d[17]), "+f"(d[18]), "+f"(d[19])
    : "l"(da), "l"(db), "r"(sc), "n"(TA), "n"(TB));
}
template<int TA, int TB> __device__ __forceinline__ void wgmma_n48(float* d, uint64_t da, uint64_t db, int sc) {
  asm volatile("{\n.reg .pred p;\nsetp.ne.b32 p, %26, 0;\n"
    "wgmma.mma_async.sync.aligned.m64n48k16.f32.bf16.bf16 {%0, %1, %2, %3, %4, %5, %6, %7, %8, %9, %10, %11, %12, %13, %14, %15, %16, %17, %18, %19, %20, %21, %22, %23}, %24, %25, p, 1, 1, %27, %28;\n}\n"
    : "+f"(d[0]), "+f"(d[1]), "+f"(d[2]), "+f"(d[3]), "+f"(d[4]), "+f"(d[5]), "+f"(d[6]), "+f"(d[7]), "+f"(d[8]), "+f"(d[9]), "+f"(d[10]), "+f"(d[11]), "+f"(d[12]), "+f"(d[13]), "+f"(d[14]), "+f"(d[15]), "+f"(d[16]), "+f"(d[17]), "+f"(d[18]), "+f"(d[19]), "+f"(d[20]), "+f"(d[21]), "+f"(d[22]), "+f"(d[23])
    : "l"(da), "l"(db), "r"(sc), "n"(TA), "n"(TB));
}
template<int TA, int TB> __device__ __forceinline__ void wgmma_n56(float* d, uint64_t da, uint64_t db, int sc) {
  asm volatile("{\n.reg .pred p;\nsetp.ne.b32 p, %30, 0;\n"
    "wgmma.mma_async.sync.aligned.m64n56k16.f32.bf16.bf16 {%0, %1, %2, %3, %4, %5, %6, %7, %8, %9, %10, %11, %12, %13, %14, %15, %16, %17, %18, %19, %20, %21, %22, %23, %24, %25, %26, %27}, %28, %29, p, 1, 1, %31, %32;\n}\n"
    : "+f"(d[0]), "+f"(d[1]), "+f"(d[2]), "+f"(d[3]), "+f"(d[4]), "+f"(d[5]), "+f"(d[6]), "+f"(d[7]), "+f"(d[8]), "+f"(d[9]), "+f"(d[10]), "+f"(d[11]), "+f"(d[12]), "+f"(d[13]), "+f"(d[14]), "+f"(d[15]), "+f"(d[16]), "+f"(d[17]), "+f"(d[18]), "+f"(d[19]), "+f"(d[20]), "+f"(d[21]), "+f"(d[22]), "+f"(d[23]), "+f"(d[24]), "+f"(d[25]), "+f"(d[26]), "+f"(d[27])
    : "l"(da), "l"(db), "r"(sc), "n"(TA), "n"(TB));
}
template<int TA, int TB> __device__ __forceinline__ void wgmma_n64(float* d, uint64_t da, uint64_t db, int sc) {
  asm volatile("{\n.reg .pred p;\nsetp.ne.b32 p, %34, 0;\n"
    "wgmma.mma_async.sync.aligned.m64n64k16.f32.bf16.bf16 {%0, %1, %2, %3, %4, %5, %6, %7, %8, %9, %10, %11, %12, %13, %14, %15, %16, %17, %18, %19, %20, %21, %22, %23, %24, %25, %26, %27, %28, %29, %30, %31}, %32, %33, p, 1, 1, %35, %36;\n}\n"
    : "+f"(d[0]), "+f"(d[1]), "+f"(d[2]), "+f"(d[3]), "+f"(d[4]), "+f"(d[5]), "+f"(d[6]), "+f"(d[7]), "+f"(d[8]), "+f"(d[9]), "+f"(d[10]), "+f"(d[11]), "+f"(d[12]), "+f"(d[13]), "+f"(d[14]), "+f"(d[15]), "+f"(d[16]), "+f"(d[17]), "+f"(d[18]), "+f"(d[19]), "+f"(d[20]), "+f"(d[21]), "+f"(d[22]), "+f"(d[23]), "+f"(d[24]), "+f"(d[25]), "+f"(d[26]), "+f"(d[27]), "+f"(d[28]), "+f"(d[29]), "+f"(d[30]), "+f"(d[31])
    : "l"(da), "l"(db), "r"(sc), "n"(TA), "n"(TB));
}
template<int TA, int TB> __device__ __forceinline__ void wgmma_n72(float* d, uint64_t da, uint64_t db, int sc) {
  asm volatile("{\n.reg .pred p;\nsetp.ne.b32 p, %38, 0;\n"
    "wgmma.mma_async.sync.aligned.m64n72k16.f32.bf16.bf16 {%0, %1, %2, %3, %4, %5, %6, %7, %8, %9, %10, %11, %12, %13, %14, %15, %16, %17, %18, %19, %20, %21, %22, %23, %24, %25, %26, %27, %28, %29, %30, %31, %32, %33, %34, %35}, %36, %37, p, 1, 1, %39, %40;\n}\n"
    : "+f"(d[0]), "+f"(d[1]), "+f"(d[2]), "+f"(d[3]), "+f"(d[4]), "+f"(d[5]), "+f"(d[6]), "+f"(d[7]), "+f"(d[8]), "+f"(d[9]), "+f"(d[10]), "+f"(d[11]), "+f"(d[12]), "+f"(d[13]), "+f"(d[14]), "+f"(d[15]), "+f"(d[16]), "+f"(d[17]), "+f"(d[18]), "+f"(d[19]), "+f"(d[20]), "+f"(d[21]), "+f"(d[22]), "+f"(d[23]), "+f"(d[24]), "+f"(d[25]), "+f"(d[26]), "+f"(d[27]), "+f"(d[28]), "+f"(d[29]), "+f"(d[30]), "+f"(d[31]), "+f"(d[32]), "+f"(d[33]), "+f"(d[34]), "+f"(d[35])
    : "l"(da), "l"(db), "r"(sc), "n"(TA), "n"(TB));
}
template<int TA, int TB> __device__ __forceinline__ void wgmma_n80(float* d, uint64_t da, uint64_t db, int sc) {
  asm volatile("{\n.reg .pred p;\nsetp.ne.b32 p, %42, 0;\n"
    "wgmma.mma_async.sync.aligned.m64n80k16.f32.bf16.bf16 {%0, %1, %2, %3, %4, %5, %6, %7, %8, %9, %10, %11, %12, %13, %14, %15, %16, %17, %18, %19, %20, %21, %22, %23, %24, %25, %26, %27, %28, %29, %30, %31, %32, %33, %34, %35, %36, %37, %38, %39}, %40, %41, p, 1, 1, %43, %44;\n}\n"
    : "+f"(d[0]), "+f"(d[1]), "+f"(d[2]), "+f"(d[3]), "+f"(d[4]), "+f"(d[5]), "+f"(d[6]), "+f"(d[7]), "+f"(d[8]), "+f"(d[9]), "+f"(d[10]), "+f"(d[11]), "+f"(d[12]), "+f"(d[13]), "+f"(d[14]), "+f"(d[15]), "+f"(d[16]), "+f"(d[17]), "+f"(d[18]), "+f"(d[19]), "+f"(d[20]), "+f"(d[21]), "+f"(d[22]), "+f"(d[23]), "+f"(d[24]), "+f"(d[25]), "+f"(d[26]), "+f"(d[27]), "+f"(d[28]), "+f"(d[29]), "+f"(d[30]), "+f"(d[31]), "+f"(d[32]), "+f"(d[33]), "+f"(d[34]), "+f"(d[35]), "+f"(d[36]), "+f"(d[37]), "+f"(d[38]), "+f"(d[39])
    : "l"(da), "l"(db), "r"(sc), "n"(TA), "n"(TB));
}
template<int TA, int TB> __device__ __forceinline__ void wgmma_n88(float* d, uint64_t da, uint64_t db, int sc) {
  asm volatile("{\n.reg .pred p;\nsetp.ne.b32 p, %46, 0;\n"
    "wgmma.mma_async.sync.aligned.m64n88k16.f32.bf16.bf16 {%0, %1, %2, %3, %4, %5, %6, %7, %8, %9, %10, %11, %12, %13, %14, %15, %16, %17, %18, %19, %20, %21, %22, %23, %24, %25, %26, %27, %28, %29, %30, %31, %32, %33, %34, %35, %36, %37, %38, %39, %40, %41, %42, %43}, %44, %45, p, 1, 1, %47, %48;\n}\n"
    : "+f"(d[0]), "+f"(d[1]), "+f"(d[2]), "+f"(d[3]), "+f"(d[4]), "+f"(d[5]), "+f"(d[6]), "+f"(d[7]), "+f"(d[8]), "+f"(d[9]), "+f"(d[10]), "+f"(d[11]), "+f"(d[12]), "+f"(d[13]), "+f"(d[14]), "+f"(d[15]), "+f"(d[16]), "+f"(d[17]), "+f"(d[18]), "+f"(d[19]), "+f"(d[20]), "+f"(d[21]), "+f"(d[22]), "+f"(d[23]), "+f"(d[24]), "+f"(d[25]), "+f"(d[26]), "+f"(d[27]), "+f"(d[28]), "+f"(d[29]), "+f"(d[30]), "+f"(d[31]), "+f"(d[32]), "+f"(d[33]), "+f"(d[34]), "+f"(d[35]), "+f"(d[36]), "+f"(d[37]), "+f"(d[38]), "+f"(d[39]), "+f"(d[40]), "+f"(d[41]), "+f"(d[42]), "+f"(d[43])
    : "l"(da), "l"(db), "r"(sc), "n"(TA), "n"(TB));
}
template<int TA, int TB> __device__ __forceinline__ void wgmma_n96(float* d, uint64_t da, uint64_t db, int sc) {
  asm volatile("{\n.reg .pred p;\nsetp.ne.b32 p, %50, 0;\n"
    "wgmma.mma_async.sync.aligned.m64n96k16.f32.bf16.bf16 {%0, %1, %2, %3, %4, %5, %6, %7, %8, %9, %10, %11, %12, %13, %14, %15, %16, %17, %18, %19, %20, %21, %22, %23, %24, %25, %26, %27, %28, %29, %30, %31, %32, %33, %34, %35, %36, %37, %38, %39, %40, %41, %42, %43, %44, %45, %46, %47}, %48, %49, p, 1, 1, %51, %52;\n}\n"
    : "+f"(d[0]), "+f"(d[1]), "+f"(d[2]), "+f"(d[3]), "+f"(d[4]), "+f"(d[5]), "+f"(d[6]), "+f"(d[7]), "+f"(d[8]), "+f"(d[9]), "+f"(d[10]), "+f"(d[11]), "+f"(d[12]), "+f"(d[13]), "+f"(d[14]), "+f"(d[15]), "+f"(d[16]), "+f"(d[17]), "+f"(d[18]), "+f"(d[19]), "+f"(d[20]), "+f"(d[21]), "+f"(d[22]), "+f"(d[23]), "+f"(d[24]), "+f"(d[25]), "+f"(d[26]), "+f"(d[27]), "+f"(d[28]), "+f"(d[29]), "+f"(d[30]), "+f"(d[31]), "+f"(d[32]), "+f"(d[33]), "+f"(d[34]), "+f"(d[35]), "+f"(d[36]), "+f"(d[37]), "+f"(d[38]), "+f"(d[39]), "+f"(d[40]), "+f"(d[41]), "+f"(d[42]), "+f"(d[43]), "+f"(d[44]), "+f"(d[45]), "+f"(d[46]), "+f"(d[47])
    : "l"(da), "l"(db), "r"(sc), "n"(TA), "n"(TB));
}
template<int TA, int TB> __device__ __forceinline__ void wgmma_n104(float* d, uint64_t da, uint64_t db, int sc) {
  asm volatile("{\n.reg .pred p;\nsetp.ne.b32 p, %54, 0;\n"
    "wgmma.mma_async.sync.aligned.m64n104k16.f32.bf16.bf16 {%0, %1, %2, %3, %4, %5, %6, %7, %8, %9, %10, %11, %12, %13, %14, %15, %16, %17, %18, %19, %20, %21, %22, %23, %24, %25, %26, %27, %28, %29, %30, %31, %32, %33, %34, %35, %36, %37, %38, %39, %40, %41, %42, %43, %44, %45, %46, %47, %48, %49, %50, %51}, %52, %53, p, 1, 1, %55, %56;\n}\n"
    : "+f"(d[0]), "+f"(d[1]), "+f"(d[2]), "+f"(d[3]), "+f"(d[4]), "+f"(d[5]), "+f"(d[6]), "+f"(d[7]), "+f"(d[8]), "+f"(d[9]), "+f"(d[10]), "+f"(d[11]), "+f"(d[12]), "+f"(d[13]), "+f"(d[14]), "+f"(d[15]), "+f"(d[16]), "+f"(d[17]), "+f"(d[18]), "+f"(d[19]), "+f"(d[20]), "+f"(d[21]), "+f"(d[22]), "+f"(d[23]), "+f"(d[24]), "+f"(d[25]), "+f"(d[26]), "+f"(d[27]), "+f"(d[28]), "+f"(d[29]), "+f"(d[30]), "+f"(d[31]), "+f"(d[32]), "+f"(d[33]), "+f"(d[34]), "+f"(d[35]), "+f"(d[36]), "+f"(d[37]), "+f"(d[38]), "+f"(d[39]), "+f"(d[40]), "+f"(d[41]), "+f"(d[42]), "+f"(d[43]), "+f"(d[44]), "+f"(d[45]), "+f"(d[46]), "+f"(d[47]), "+f"(d[48]), "+f"(d[49]), "+f"(d[50]), "+f"(d[51])
    : "l"(da), "l"(db), "r"(sc), "n"(TA), "n"(TB));
}
template<int TA, int TB> __device__ __forceinline__ void wgmma_n112(float* d, uint64_t da, uint64_t db, int sc) {
  asm volatile("{\n.reg .pred p;\nsetp.ne.b32 p, %58, 0;\n"
    "wgmma.mma_async.sync.aligned.m64n112k16.f32.bf16.bf16 {%0, %1, %2, %3, %4, %5, %6, %7, %8, %9, %10, %11, %12, %13, %14, %15, %16, %17, %18, %19, %20, %21, %22, %23, %24, %25, %26, %27, %28, %29, %30, %31, %32, %33, %34, %35, %36, %37, %38, %39, %40, %41, %42, %43, %44, %45, %46, %47, %48, %49, %50, %51, %52, %53, %54, %55}, %56, %57, p, 1, 1, %59, %60;\n}\n"
    : "+f"(d[0]), "+f"(d[1]), "+f"(d[2]), "+f"(d[3]), "+f"(d[4]), "+f"(d[5]), "+f"(d[6]), "+f"(d[7]), "+f"(d[8]), "+f"(d[9]), "+f"(d[10]), "+f"(d[11]), "+f"(d[12]), "+f"(d[13]), "+f"(d[14]), "+f"(d[15]), "+f"(d[16]), "+f"(d[17]), "+f"(d[18]), "+f"(d[19]), "+f"(d[20]), "+f"(d[21]), "+f"(d[22]), "+f"(d[23]), "+f"(d[24]), "+f"(d[25]), "+f"(d[26]), "+f"(d[27]), "+f"(d[28]), "+f"(d[29]), "+f"(d[30]), "+f"(d[31]), "+f"(d[32]), "+f"(d[33]), "+f"(d[34]), "+f"(d[35]), "+f"(d[36]), "+f"(d[37]), "+f"(d[38]), "+f"(d[39]), "+f"(d[40]), "+f"(d[41]), "+f"(d[42]), "+f"(d[43]), "+f"(d[44]), "+f"(d[45]), "+f"(d[46]), "+f"(d[47]), "+f"(d[48]), "+f"(d[49]), "+f"(d[50]), "+f"(d[51]), "+f"(d[52]), "+f"(d[53]), "+f"(d[54]), "+f"(d[55])
    : "l"(da), "l"(db), "r"(sc), "n"(TA), "n"(TB));
}
template<int TA, int TB> __device__ __forceinline__ void wgmma_n120(float* d, uint64_t da, uint64_t db, int sc) {
  asm volatile("{\n.reg .pred p;\nsetp.ne.b32 p, %62, 0;\n"
    "wgmma.mma_async.sync.aligned.m64n120k16.f32.bf16.bf16 {%0, %1, %2, %3, %4, %5, %6, %7, %8, %9, %10, %11, %12, %13, %14, %15, %16, %17, %18, %19, %20, %21, %22, %23, %24, %25, %26, %27, %28, %29, %30, %31, %32, %33, %34, %35, %36, %37, %38, %39, %40, %41, %42, %43, %44, %45, %46, %47, %48, %49, %50, %51, %52, %53, %54, %55, %56, %57, %58, %59}, %60, %61, p, 1, 1, %63, %64;\n}\n"
    : "+f"(d[0]), "+f"(d[1]), "+f"(d[2]), "+f"(d[3]), "+f"(d[4]), "+f"(d[5]), "+f"(d[6]), "+f"(d[7]), "+f"(d[8]), "+f"(d[9]), "+f"(d[10]), "+f"(d[11]), "+f"(d[12]), "+f"(d[13]), "+f"(d[14]), "+f"(d[15]), "+f"(d[16]), "+f"(d[17]), "+f"(d[18]), "+f"(d[19]), "+f"(d[20]), "+f"(d[21]), "+f"(d[22]), "+f"(d[23]), "+f"(d[24]), "+f"(d[25]), "+f"(d[26]), "+f"(d[27]), "+f"(d[28]), "+f"(d[29]), "+f"(d[30]), "+f"(d[31]), "+f"(d[32]), "+f"(d[33]), "+f"(d[34]), "+f"(d[35]), "+f"(d[36]), "+f"(d[37]), "+f"(d[38]), "+f"(d[39]), "+f"(d[40]), "+f"(d[41]), "+f"(d[42]), "+f"(d[43]), "+f"(d[44]), "+f"(d[45]), "+f"(d[46]), "+f"(d[47]), "+f"(d[48]), "+f"(d[49]), "+f"(d[50]), "+f"(d[51]), "+f"(d[52]), "+f"(d[53]), "+f"(d[54]), "+f"(d[55]), "+f"(d[56]), "+f"(d[57]), "+f"(d[58]), "+f"(d[59])
    : "l"(da), "l"(db), "r"(sc), "n"(TA), "n"(TB));
}
template<int TA, int TB> __device__ __forceinline__ void wgmma_n128(float* d, uint64_t da, uint64_t db, int sc) {
  asm volatile("{\n.reg .pred p;\nsetp.ne.b32 p, %66, 0;\n"
    "wgmma.mma_async.sync.aligned.m64n128k16.f32.bf16.bf16 {%0, %1, %2, %3, %4, %5, %6, %7, %8, %9, %10, %11, %12, %13, %14, %15, %16, %17, %18, %19, %20, %21, %22, %23, %24, %25, %26, %27, %28, %29, %30, %31, %32, %33, %34, %35, %36, %37, %38, %39, %40, %41, %42, %43, %44, %45, %46, %47, %48, %49, %50, %51, %52, %53, %54, %55, %56, %57, %58, %59, %60, %61, %62, %63}, %64, %65, p, 1, 1, %67, %68;\n}\n"
    : "+f"(d[0]), "+f"(d[1]), "+f"(d[2]), "+f"(d[3]), "+f"(d[4]), "+f"(d[5]), "+f"(d[6]), "+f"(d[7]), "+f"(d[8]), "+f"(d[9]), "+f"(d[10]), "+f"(d[11]), "+f"(d[12]), "+f"(d[13]), "+f"(d[14]), "+f"(d[15]), "+f"(d[16]), "+f"(d[17]), "+f"(d[18]), "+f"(d[19]), "+f"(d[20]), "+f"(d[21]), "+f"(d[22]), "+f"(d[23]), "+f"(d[24]), "+f"(d[25]), "+f"(d[26]), "+f"(d[27]), "+f"(d[28]), "+f"(d[29]), "+f"(d[30]), "+f"(d[31]), "+f"(d[32]), "+f"(d[33]), "+f"(d[34]), "+f"(d[35]), "+f"(d[36]), "+f"(d[37]), "+f"(d[38]), "+f"(d[39]), "+f"(d[40]), "+f"(d[41]), "+f"(d[42]), "+f"(d[43]), "+f"(d[44]), "+f"(d[45]), "+f"(d[46]), "+f"(d[47]), "+f"(d[48]), "+f"(d[49]), "+f"(d[50]), "+f"(d[51]), "+f"(d[52]), "+f"(d[53]), "+f"(d[54]), "+f"(d[55]), "+f"(d[56]), "+f"(d[57]), "+f"(d[58]), "+f"(d[59]), "+f"(d[60]), "+f"(d[61]), "+f"(d[62]), "+f"(d[63])
    : "l"(da), "l"(db), "r"(sc), "n"(TA), "n"(TB));
}
template<int TA, int TB> __device__ __forceinline__ void wgmma_n160(float* d, uint64_t da, uint64_t db, int sc) {
  asm volatile("{\n.reg .pred p;\nsetp.ne.b32 p, %82, 0;\n"
    "wgmma.mma_async.sync.aligned.m64n160k16.f32.bf16.bf16 {%0, %1, %2, %3, %4, %5, %6, %7, %8, %9, %10, %11, %12, %13, %14, %15, %16, %17, %18, %19, %20, %21, %22, %23, %24, %25, %26, %27, %28, %29, %30, %31, %32, %33, %34, %35, %36, %37, %38, %39, %40, %41, %42, %43, %44, %45, %46, %47, %48, %49, %50, %51, %52, %53, %54, %55, %56, %57, %58, %59, %60, %61, %62, %63, %64, %65, %66, %67, %68, %69, %70, %71, %72, %73, %74, %75, %76, %77, %78, %79}, %80, %81, p, 1, 1, %83, %84;\n}\n"
    : "+f"(d[0]), "+f"(d[1]), "+f"(d[2]), "+f"(d[3]), "+f"(d[4]), "+f"(d[5]), "+f"(d[6]), "+f"(d[7]), "+f"(d[8]), "+f"(d[9]), "+f"(d[10]), "+f"(d[11]), "+f"(d[12]), "+f"(d[13]), "+f"(d[14]), "+f"(d[15]), "+f"(d[16]), "+f"(d[17]), "+f"(d[18]), "+f"(d[19]), "+f"(d[20]), "+f"(d[21]), "+f"(d[22]), "+f"(d[23]), "+f"(d[24]), "+f"(d[25]), "+f"(d[26]), "+f"(d[27]), "+f"(d[28]), "+f"(d[29]), "+f"(d[30]), "+f"(d[31]), "+f"(d[32]), "+f"(d[33]), "+f"(d[34]), "+f"(d[35]), "+f"(d[36]), "+f"(d[37]), "+f"(d[38]), "+f"(d[39]), "+f"(d[40]), "+f"(d[41]), "+f"(d[42]), "+f"(d[43]), "+f"(d[44]), "+f"(d[45]), "+f"(d[46]), "+f"(d[47]), "+f"(d[48]), "+f"(d[49]), "+f"(d[50]), "+f"(d[51]), "+f"(d[52]), "+f"(d[53]), "+f"(d[54]), "+f"(d[55]), "+f"(d[56]), "+f"(d[57]), "+f"(d[58]), "+f"(d[59]), "+f"(d[60]), "+f"(d[61]), "+f"(d[62]), "+f"(d[63]), "+f"(d[64]), "+f"(d[65]), "+f"(d[66]), "+f"(d[67]), "+f"(d[68]), "+f"(d[69]), "+f"(d[70]), "+f"(d[71]), "+f"(d[72]), "+f"(d[73]), "+f"(d[74]), "+f"(d[75]), "+f"(d[76]), "+f"(d[77]), "+f"(d[78]), "+f"(d[79])
    : "l"(da), "l"(db), "r"(sc), "n"(TA), "n"(TB));
}
template<int TA, int TB> __device__ __forceinline__ void wgmma_n192(float* d, uint64_t da, uint64_t db, int sc) {
  asm volatile("{\n.reg .pred p;\nsetp.ne.b32 p, %98, 0;\n"
    "wgmma.mma_async.sync.aligned.m64n192k16.f32.bf16.bf16 {%0, %1, %2, %3, %4, %5, %6, %7, %8, %9, %10, %11, %12, %13, %14, %15, %16, %17, %18, %19, %20, %21, %22, %23, %24, %25, %26, %27, %28, %29, %30, %31, %32, %33, %34, %35, %36, %37, %38, %39, %40, %41, %42, %43, %44, %45, %46, %47, %48, %49, %50, %51, %52, %53, %54, %55, %56, %57, %58, %59, %60, %61, %62, %63, %64, %65, %66, %67, %68, %69, %70, %71, %72, %73, %74, %75, %76, %77, %78, %79, %80, %81, %82, %83, %84, %85, %86, %87, %88, %89, %90, %91, %92, %93, %94, %95}, %96, %97, p, 1, 1, %99, %100;\n}\n"
    : "+f"(d[0]), "+f"(d[1]), "+f"(d[2]), "+f"(d[3]), "+f"(d[4]), "+f"(d[5]), "+f"(d[6]), "+f"(d[7]), "+f"(d[8]), "+f"(d[9]), "+f"(d[10]), "+f"(d[11]), "+f"(d[12]), "+f"(d[13]), "+f"(d[14]), "+f"(d[15]), "+f"(d[16]), "+f"(d[17]), "+f"(d[18]), "+f"(d[19]), "+f"(d[20]), "+f"(d[21]), "+f"(d[22]), "+f"(d[23]), "+f"(d[24]), "+f"(d[25]), "+f"(d[26]), "+f"(d[27]), "+f"(d[28]), "+f"(d[29]), "+f"(d[30]), "+f"(d[31]), "+f"(d[32]), "+f"(d[33]), "+f"(d[34]), "+f"(d[35]), "+f"(d[36]), "+f"(d[37]), "+f"(d[38]), "+f"(d[39]), "+f"(d[40]), "+f"(d[41]), "+f"(d[42]), "+f"(d[43]), "+f"(d[44]), "+f"(d[45]), "+f"(d[46]), "+f"(d[47]), "+f"(d[48]), "+f"(d[49]), "+f"(d[50]), "+f"(d[51]), "+f"(d[52]), "+f"(d[53]), "+f"(d[54]), "+f"(d[55]), "+f"(d[56]), "+f"(d[57]), "+f"(d[58]), "+f"(d[59]), "+f"(d[60]), "+f"(d[61]), "+f"(d[62]), "+f"(d[63]), "+f"(d[64]), "+f"(d[65]), "+f"(d[66]), "+f"(d[67]), "+f"(d[68]), "+f"(d[69]), "+f"(d[70]), "+f"(d[71]), "+f"(d[72]), "+f"(d[73]), "+f"(d[74]), "+f"(d[75]), "+f"(d[76]), "+f"(d[77]), "+f"(d[78]), "+f"(d[79]), "+f"(d[80]), "+f"(d[81]), "+f"(d[82]), "+f"(d[83]), "+f"(d[84]), "+f"(d[85]), "+f"(d[86]), "+f"(d[87]), "+f"(d[88]), "+f"(d[89]), "+f"(d[90]), "+f"(d[91]), "+f"(d[92]), "+f"(d[93]), "+f"(d[94]), "+f"(d[95])
    : "l"(da), "l"(db), "r"(sc), "n"(TA), "n"(TB));
}
template<int N, int TA, int TB> __device__ __forceinline__ void wgmma_ss(float* d, uint64_t da, uint64_t db, int sc) {
  if constexpr (N == 8) wgmma_n8<TA,TB>(d, da, db, sc);
  if constexpr (N == 16) wgmma_n16<TA,TB>(d, da, db, sc);
  if constexpr (N == 24) wgmma_n24<TA,TB>(d, da, db, sc);
  if constexpr (N == 32) wgmma_n32<TA,TB>(d, da, db, sc);
  if constexpr (N == 40) wgmma_n40<TA,TB>(d, da, db, sc);
  if constexpr (N == 48) wgmma_n48<TA,TB>(d, da, db, sc);
  if constexpr (N == 56) wgmma_n56<TA,TB>(d, da, db, sc);
  if constexpr (N == 64) wgmma_n64<TA,TB>(d, da, db, sc);
  if constexpr (N == 72) wgmma_n72<TA,TB>(d, da, db, sc);
  if constexpr (N == 80) wgmma_n80<TA,TB>(d, da, db, sc);
  if constexpr (N == 88) wgmma_n88<TA,TB>(d, da, db, sc);
  if constexpr (N == 96) wgmma_n96<TA,TB>(d, da, db, sc);
  if constexpr (N == 104) wgmma_n104<TA,TB>(d, da, db, sc);
  if constexpr (N == 112) wgmma_n112<TA,TB>(d, da, db, sc);
  if constexpr (N == 120) wgmma_n120<TA,TB>(d, da, db, sc);
  if constexpr (N == 128) wgmma_n128<TA,TB>(d, da, db, sc);
  if constexpr (N == 160) wgmma_n160<TA,TB>(d, da, db, sc);
  if constexpr (N == 192) wgmma_n192<TA,TB>(d, da, db, sc);
}

constexpr int NGRP = 260;
constexpr uint32_t G1_STAGE = 57344;
constexpr uint32_t OFF_U = 131072;
constexpr uint32_t OFF_H = 172032;
constexpr uint32_t H_PITCH = 4352;
constexpr uint32_t OFF_ZS = 215552;
constexpr uint32_t OFF_EX = OFF_ZS + 12288;
constexpr uint32_t OFF_G = OFF_EX + 2560;
constexpr uint32_t OFF_BAR = OFF_G + 640;
constexpr uint32_t OFF_GS = OFF_BAR + 384;
constexpr uint32_t SMEM_BYTES = OFF_GS + 64;
constexpr uint32_t OFF_V = OFF_H + 23040;
constexpr uint32_t OFF_US = OFF_ZS + 1536;
constexpr int NCTA = 130;

enum { B_FULL1 = 0, B_KV = 3,
       B_FULL2 = 4, B_EMPTY2 = 8, B_CD = 12, B_HLD = 17, B_QZ = 18, B_GATE = 19, B_GS = 20,
       B_HDR = 21, B_XF = 22, B_XCH = 23,
       B_EMPTY1 = 24, B_G1DONE = 27,
       B_R2FREE = 28, B_UFULL = 29,
       B_SIGH = 34, B_SIGZ = 38, B_COUNT = 43 };
enum { C_H = 0, C_U = 16, C_Z = 24, C_DONE = 34, C_COUNT = 35 };
__host__ __device__ constexpr uint32_t slotF(int s) { return s == 0 ? 114688 : s == 1 ? 32768 : s == 2 ? 90112 : 49152; }
__host__ __device__ constexpr uint32_t slotO(int s) { return s == 3 ? 106496 : slotF(s) + 8192; }
__host__ __device__ constexpr uint32_t slotB0(int s) { return s == 0 ? 0 : s == 1 ? 20480 : s == 2 ? 67584 : 155648; }
__host__ __device__ constexpr uint32_t slotB1(int s) { return s == 1 ? 57344 : slotB0(s) + 10240; }
constexpr uint32_t OFF_Q = 176128, OFF_Z = 131072, OFF_XCH = 196608;
__device__ __forceinline__ uint32_t zstage(int ch) { return ch < 3 ? OFF_ZS + ch * 4096 : ch == 3 ? 198656 : 208896; }

__device__ __align__(1024) __nv_bfloat16 g_Hs[48 * NGRP * 256];
__device__ __align__(1024) __nv_bfloat16 g_U[640 * 2 * 2048];
__device__ __align__(1024) __nv_bfloat16 g_zT[640 * NGRP * 8];
__device__ __align__(1024) float g_gate[NGRP * 8];
__device__ __align__(1024) unsigned g_cnt[C_COUNT * 32];
#define TS(i) do { } while (0)

__device__ __forceinline__ uint32_t smem_u32(const void* p) { return (uint32_t)__cvta_generic_to_shared(p); }
__device__ __forceinline__ uint64_t mkdesc(uint32_t addr, uint32_t lbo, uint32_t sbo, uint32_t swz) {
  return (uint64_t)((addr & 0x3FFFF) >> 4) | ((uint64_t)(lbo >> 4) << 16) | ((uint64_t)(sbo >> 4) << 32) | ((uint64_t)swz << 62);
}
__device__ __forceinline__ void wg_fence() { asm volatile("wgmma.fence.sync.aligned;" ::: "memory"); }
__device__ __forceinline__ void wg_commit() { asm volatile("wgmma.commit_group.sync.aligned;" ::: "memory"); }
template <int N> __device__ __forceinline__ void wg_wait() { asm volatile("wgmma.wait_group.sync.aligned %0;" ::"n"(N) : "memory"); }
template <int N> __device__ __forceinline__ void pin(float* d) {
#pragma unroll
  for (int i = 0; i < N; i++) asm volatile("" : "+f"(d[i])::"memory");
}
__device__ __forceinline__ void mbar_init(uint32_t a, int c) { asm volatile("mbarrier.init.shared::cta.b64 [%0], %1;" ::"r"(a), "r"(c) : "memory"); }
__device__ __forceinline__ void mbar_expect(uint32_t a, uint32_t b) { asm volatile("mbarrier.arrive.expect_tx.shared::cta.b64 _, [%0], %1;" ::"r"(a), "r"(b) : "memory"); }
__device__ __forceinline__ uint32_t peer_addr(uint32_t a) {
  uint32_t r;
  asm("mapa.shared::cluster.u32 %0, %1, %2;" : "=r"(r) : "r"(a), "r"((blockIdx.x & 1) ^ 1));
  return r;
}
__device__ __forceinline__ void mbar_arrive(uint32_t a) { asm volatile("mbarrier.arrive.shared::cta.b64 _, [%0];" ::"r"(a) : "memory"); }
__device__ __forceinline__ void mbar_wait_t(uint32_t a, uint32_t ph) {
  uint32_t ok;
  int it = 0;
  do {
    asm volatile("{\n.reg .pred p;\nmbarrier.try_wait.parity.shared::cta.b64 p, [%1], %2;\nselp.u32 %0,1,0,p;\n}" : "=r"(ok) : "r"(a), "r"(ph) : "memory");
    if (++it > (1 << 18)) __trap();
  } while (!ok);
}
__device__ __forceinline__ void mbar_wait(uint32_t a, uint32_t ph) {
  asm volatile(
      "{\n.reg .pred p, q;\n.reg .u32 n;\nmov.u32 n, 0;\n"
      "WAIT_%=:\n"
      "mbarrier.try_wait.parity.shared::cta.b64 p, [%0], %1;\n"
      "@p bra DONE_%=;\n"
      "add.u32 n, n, 1;\n"
      "setp.lt.u32 q, n, 0x80000;\n"
      "@q bra WAIT_%=;\n"
      "DONE_%=:\n}" ::"r"(a), "r"(ph) : "memory");
}
__device__ __forceinline__ void flag_wait(const unsigned* p0, const unsigned* p1, unsigned target) {
  int it = 0;
  while (true) {
    unsigned v0, v1;
    asm volatile("ld.relaxed.gpu.global.u32 %0, [%1];" : "=r"(v0) : "l"(p0) : "memory");
    asm volatile("ld.relaxed.gpu.global.u32 %0, [%1];" : "=r"(v1) : "l"(p1) : "memory");
    if (min(v0, v1) >= target) break;
    if (++it > (1 << 21)) __trap();
  }
  asm volatile("fence.proxy.async.global;" ::: "memory");
}
__device__ __forceinline__ void flag_add(unsigned* p) {
  asm volatile("red.relaxed.gpu.global.add.u32 [%0], 1;" ::"l"(p) : "memory");
}
__device__ __forceinline__ void bar_sync(int id, int n) { asm volatile("bar.sync %0, %1;" ::"r"(id), "r"(n) : "memory"); }
__device__ __forceinline__ void bar_arrive(int id, int n) { asm volatile("bar.arrive %0, %1;" ::"r"(id), "r"(n) : "memory"); }
__device__ __forceinline__ void bulk_g2s(uint32_t dst, const void* src, uint32_t bytes, uint32_t bar) {
  asm volatile("cp.async.bulk.shared::cluster.global.mbarrier::complete_tx::bytes [%0], [%1], %2, [%3];" ::"r"(dst), "l"(src), "r"(bytes), "r"(bar) : "memory");
}
__device__ __forceinline__ void bulk_s2g(void* dst, uint32_t src, uint32_t bytes) {
  asm volatile("cp.async.bulk.global.shared::cta.bulk_group [%0], [%1], %2;" ::"l"(dst), "r"(src), "r"(bytes) : "memory");
}
__device__ __forceinline__ void bulk_prefetch(const void* src, uint32_t bytes) {
  asm volatile("cp.async.bulk.prefetch.L2.global [%0], %1;" ::"l"(src), "r"(bytes) : "memory");
}
__device__ __forceinline__ void tma2(uint32_t dst, const CUtensorMap* m, int c0, int c1, uint32_t bar) {
  asm volatile("cp.async.bulk.tensor.2d.shared::cluster.global.mbarrier::complete_tx::bytes [%0], [%1, {%3,%4}], [%2];" ::"r"(dst), "l"(m), "r"(bar), "r"(c0), "r"(c1) : "memory");
}
__device__ __forceinline__ void tma3(uint32_t dst, const CUtensorMap* m, int c0, int c1, int c2, uint32_t bar) {
  asm volatile("cp.async.bulk.tensor.3d.shared::cluster.global.mbarrier::complete_tx::bytes [%0], [%1, {%3,%4,%5}], [%2];" ::"r"(dst), "l"(m), "r"(bar), "r"(c0), "r"(c1), "r"(c2) : "memory");
}
__device__ __forceinline__ void tma4(uint32_t dst, const CUtensorMap* m, int c0, int c1, int c2, int c3, uint32_t bar) {
  asm volatile("cp.async.bulk.tensor.4d.shared::cluster.global.mbarrier::complete_tx::bytes [%0], [%1, {%3,%4,%5,%6}], [%2];" ::"r"(dst), "l"(m), "r"(bar), "r"(c0), "r"(c1), "r"(c2), "r"(c3) : "memory");
}
__device__ __forceinline__ void prefetch_map(const CUtensorMap* m) { asm volatile("prefetch.tensormap [%0];" ::"l"(m) : "memory"); }
__device__ __forceinline__ void tma2_store(const CUtensorMap* m, uint32_t src, int c0, int c1) {
  asm volatile("cp.async.bulk.tensor.2d.global.shared::cta.bulk_group [%0, {%2,%3}], [%1];" ::"l"(m), "r"(src), "r"(c0), "r"(c1) : "memory");
}
__device__ __forceinline__ void tma3_store(const CUtensorMap* m, uint32_t src, int c0, int c1, int c2) {
  asm volatile("cp.async.bulk.tensor.3d.global.shared::cta.bulk_group [%0, {%2,%3,%4}], [%1];" ::"l"(m), "r"(src), "r"(c0), "r"(c1), "r"(c2) : "memory");
}
__device__ __forceinline__ void tma4_store(const CUtensorMap* m, uint32_t src, int c0, int c1, int c2, int c3) {
  asm volatile("cp.async.bulk.tensor.4d.global.shared::cta.bulk_group [%0, {%2,%3,%4,%5}], [%1];" ::"l"(m), "r"(src), "r"(c0), "r"(c1), "r"(c2), "r"(c3) : "memory");
}
__device__ __forceinline__ uint32_t pack_bf16(float lo, float hi) {
  uint32_t r;
  asm("cvt.rn.bf16x2.f32 %0, %1, %2;" : "=r"(r) : "f"(hi), "f"(lo));
  return r;
}
__device__ __forceinline__ float tanh_fast(float x) {
  float r;
  asm("tanh.approx.f32 %0, %1;" : "=f"(r) : "f"(x));
  return r;
}
__device__ __forceinline__ uint32_t bmul2(uint32_t a, uint32_t b) {
  uint32_t r;
  asm("mul.rn.bf16x2 %0, %1, %2;" : "=r"(r) : "r"(a), "r"(b));
  return r;
}
__device__ __forceinline__ uint32_t bfma2(uint32_t a, uint32_t b, uint32_t c) {
  uint32_t r;
  asm("fma.rn.bf16x2 %0, %1, %2, %3;" : "=r"(r) : "r"(a), "r"(b), "r"(c));
  return r;
}
__device__ __forceinline__ uint2 lds64(uint32_t a) {
  uint2 r;
  asm volatile("ld.volatile.shared.v2.u32 {%0,%1}, [%2];" : "=r"(r.x), "=r"(r.y) : "r"(a) : "memory");
  return r;
}
__device__ __forceinline__ float bflo(uint32_t v) { return __uint_as_float(v << 16); }
__device__ __forceinline__ float bfhi(uint32_t v) { return __uint_as_float(v & 0xffff0000u); }

template <int S> struct ConvSteps {
  static __device__ __forceinline__ void run(float* d, uint64_t da, uint64_t db, int first) {
    wgmma_ss<128 - 8 * S, 1, 1>(d, da + 16 * S, db + 16 * S, S == 0 ? first : 1);
    if constexpr (S + 1 < 16) ConvSteps<S + 1>::run(d, da, db, first);
  }
};

__device__ __forceinline__ void conv_issue(float* d, uint32_t sb, int ch) {
  const uint64_t da = mkdesc(sb + OFF_H + ch * 2 * H_PITCH, 128, 32, 0);
  const uint64_t db = mkdesc(sb + OFF_U + (4 - ch) * 8192, 128, 256, 0);
  wg_fence();
  ConvSteps<0>::run(d, da, db, 0);
  ConvSteps<0>::run(d, da + (H_PITCH >> 4), db + 256, 1);
}
__device__ __forceinline__ void conv_finish(const float* d, unsigned char* sm, uint32_t bar, int ch, int wg, int w, int lane) {
  const int g = lane >> 2, q = lane & 3;
  const int c = q & 1, mu = 8 * (q >> 1) + g;
  const int mu1 = (mu + 15) & 15, mu2 = (mu + (c ? 2 : 14)) & 15;
  const int src1 = 4 * (mu1 & 7) + 2 * (mu1 >> 3) + c;
  const int src2 = 4 * (mu2 & 7) + 2 * (mu2 >> 3) + (c ^ 1);
  const bool last = mu == 15, pA = (c == 0) || (mu >= 14);
  const bool impX = lane < 2, impY = (c == 1) && (mu >= 14);
  const int slot = impX ? lane : 2 + (mu & 1);
  const int oo = 32 * w + (c ? mu2 : 16 + mu);
  float xr[16], s1[16];
#pragma unroll
  for (int J = 0; J < 16; J++) {
    const int i = 4 * (15 - J);
    float a = last ? d[i + 1] : d[i + 3];
    float b = last ? d[i + 3] : d[i + 1];
    s1[J] = d[i + 2] + __shfl_sync(0xffffffffu, a, src1);
    xr[J] = __shfl_sync(0xffffffffu, b, src1);
  }
  const uint32_t zs = zstage(ch);
  const int ep = ch < 3 ? 128 : 80;
  float* ex = reinterpret_cast<float*>(sm + (ch < 3 ? zs : OFF_EX + (ch - 3) * 1280)) + slot * 20;
  if (impX || impY) {
    if (w < 3) {
      float* e = ex + (w + 1) * ep;
#pragma unroll
      for (int J = 0; J < 16; J += 4)
        *reinterpret_cast<float4*>(e + J) = impX ? make_float4(xr[J], xr[J + 1], xr[J + 2], xr[J + 3]) : make_float4(s1[J], s1[J + 1], s1[J + 2], s1[J + 3]);
    } else {
      *reinterpret_cast<float4*>(ex) = impX ? make_float4(0.f, xr[0], xr[1], xr[2]) : make_float4(0.f, s1[0], s1[1], s1[2]);
#pragma unroll
      for (int J = 4; J < 16; J += 4)
        *reinterpret_cast<float4*>(ex + J) = impX ? make_float4(xr[J - 1], xr[J], xr[J + 1], xr[J + 2]) : make_float4(s1[J - 1], s1[J], s1[J + 1], s1[J + 2]);
    }
  }
  bar_sync(3 + wg, 128);
  if (w == 0 && lane == 0) mbar_arrive(bar + 8 * (B_CD + ch));
  if (impX || impY) {
    const float* e = ex + w * ep;
#pragma unroll
    for (int J = 0; J < 16; J += 4) {
      float4 v = *reinterpret_cast<const float4*>(e + J);
      if (impX) { xr[J] = v.x; xr[J + 1] = v.y; xr[J + 2] = v.z; xr[J + 3] = v.w; }
      else { s1[J] = v.x; s1[J + 1] = v.y; s1[J + 2] = v.z; s1[J + 3] = v.w; }
    }
  }
  float y[16];
#pragma unroll
  for (int J = 0; J < 16; J++) {
    const float s0 = d[4 * (15 - J)] + xr[J];
    const float snd = pA ? s0 : s1[J];
    const float own = pA ? s1[J] : s0;
    y[J] = own + __shfl_sync(0xffffffffu, snd, src2);
  }
  unsigned char* zd = sm + zs + oo * 16;
  *reinterpret_cast<uint4*>(zd) = make_uint4(pack_bf16(y[0], y[1]), pack_bf16(y[2], y[3]), pack_bf16(y[4], y[5]), pack_bf16(y[6], y[7]));
  *reinterpret_cast<uint4*>(zd + 2048) = make_uint4(pack_bf16(y[8], y[9]), pack_bf16(y[10], y[11]), pack_bf16(y[12], y[13]), pack_bf16(y[14], y[15]));
  asm volatile("fence.proxy.async.shared::cta;" ::: "memory");
  __syncwarp();
  if (lane == 0) mbar_arrive(bar + 8 * (B_SIGZ + ch));
}
template <int S, int OWN, int K0 = 0, int K1 = 4> __device__ __forceinline__ void g2_half(float* acc, uint64_t dA, uint64_t dB, int sc) {
#pragma unroll
  for (int kk = K0; kk < K1; kk++)
    wgmma_ss<160, 1, 0>(acc, dA + (((OWN ? slotO(S) : slotF(S)) >> 4) + 128 * kk), dB + (((kk < 2 ? slotB0(S) : slotB1(S)) >> 4) + 2 * (kk & 1)), kk ? 1 : sc);
}

__device__ __forceinline__ void glu_store(const float* acc, uint32_t dst) {
#pragma unroll
  for (int h = 0; h < 2; h++) {
#pragma unroll
    for (int aa = 0; aa < 3; aa++) {
      uint32_t v[4];
#pragma unroll
      for (int jj = 0; jj < 4; jj++) {
        const int i = 4 * (4 * aa + jj) + 2 * h;
        float t0 = tanh_fast(0.5f * acc[i]), t1 = tanh_fast(0.5f * acc[i + 1]);
        v[jj] = pack_bf16(fmaf(acc[48 + i], t0, acc[48 + i]), fmaf(acc[49 + i], t1, acc[49 + i]));
      }
      asm volatile("stmatrix.sync.aligned.m8n8.x4.shared.b16 [%0], {%1,%2,%3,%4};" ::"r"(dst + h * 1536 + aa * 512), "r"(v[0]), "r"(v[1]), "r"(v[2]), "r"(v[3]) : "memory");
    }
  }
}

struct Params {
  const __nv_bfloat16 *q, *k, *v, *w_gate, *w_up, *w_down, *shift_k, *ssm_k, *ssm_D, *gate_w;
  unsigned char perm[72];
};

__global__ void __cluster_dims__(2, 1, 1) __launch_bounds__(384, 1)
fused_kernel(const __grid_constant__ CUtensorMap mX, const __grid_constant__ CUtensorMap mWg,
             const __grid_constant__ CUtensorMap mWu, const __grid_constant__ CUtensorMap mWd,
             const __grid_constant__ CUtensorMap mQ, const __grid_constant__ CUtensorMap mZ,
             const __grid_constant__ CUtensorMap mO, const __grid_constant__ CUtensorMap mK,
             const __grid_constant__ CUtensorMap mV, const __grid_constant__ CUtensorMap mU,
             const __grid_constant__ CUtensorMap mH, const Params P) {
  extern __shared__ __align__(1024) unsigned char sm[];
  const uint32_t sb = smem_u32(sm);
  const uint32_t bar = sb + OFF_BAR;
  const int tid = threadIdx.x, warp = __shfl_sync(0xffffffffu, tid >> 5, 0), lane = tid & 31;
  const int p2 = P.perm[blockIdx.x >> 1];
  const int cta = (p2 & 64) * 2 + (((p2 >> 1) & 4) | (p2 & 3)) * 16 + (((p2 >> 3) & 6) | ((p2 >> 2) & 1)) * 2 + (blockIdx.x & 1);
  const bool has1 = cta < 128;
  const int mb = cta >> 4, ft = cta & 15;
  const int rank = cta & 1;
  const int db = 2 * (p2 % 5) + rank;
  const int tb = p2 / 5;

  if (lane == 0) {
    if (warp == 8) {
      if (has1) {
#pragma unroll
        for (int kb = 0; kb < 3; kb++) {
          const int rg = (kb + 1) % 3;
          const uint32_t dst = sb + rg * G1_STAGE, fb = bar + 8 * (B_FULL1 + rg);
          mbar_init(fb, 1);
          mbar_expect(fb, G1_STAGE + (kb == 0 ? 1280 : 0));
          asm volatile("fence.proxy.async.shared::cta;" ::: "memory");
          tma4(dst, &mX, kb * 64, 0, (mb & 3) * 32, mb >> 2, fb);
          tma3(dst + 32768, &mWg, 0, kb * 64, ft * 3, fb);
          tma3(dst + 32768 + 12288, &mWu, 0, kb * 64, ft * 3, fb);
          if (kb == 0) bulk_g2s(sb + OFF_EX + 640, P.gate_w, 1280, fb);
        }
        mbar_init(bar + 8 * B_KV, 1);
        mbar_expect(bar + 8 * B_KV, 23040 + 21760 + 640);
        asm volatile("fence.proxy.async.shared::cta;" ::: "memory");
      }
    } else {
      if (warp > 8) prefetch_map(warp == 9 ? &mWg : warp == 10 ? &mWu : &mK);
#pragma unroll
      for (int j = 0; j < 4; j++) {
        const int i = B_FULL2 + (warp > 8 ? warp - 1 : warp) + 11 * j;
        if (i < B_COUNT) mbar_init(bar + 8 * i, i < B_EMPTY1 ? 1 : i < B_R2FREE ? 2 : i < B_SIGH ? 3 : 4);
        if (i == B_XCH) mbar_expect(bar + 8 * B_XCH, 20480);
      }
      asm volatile("fence.proxy.async.shared::cta;" ::: "memory");
    }
  }
  __syncthreads();
  if (warp != 11) asm volatile("barrier.cluster.arrive.relaxed.aligned;" ::: "memory");

  if (warp < 8) {
    asm volatile("setmaxnreg.inc.sync.aligned.u32 224;");
    const int wg = warp >> 2, w = warp & 3;
    const bool elect = (tid & 127) == 0;
    if (has1) {
      float acc0[96], acc1[96];
      float *const d0 = acc0, *const d1 = acc1;
      {
        const uint64_t dA = mkdesc(sb + wg * 16384, 16, 1024, 1);
        const uint64_t dB = mkdesc(sb + 32768, 4096, 512, 2);
#pragma unroll 1
        for (int kb = 0; kb < 8; kb++) {
          const int rg = (kb + 1) % 3;
          const uint64_t da = dA + rg * (G1_STAGE >> 4), db = dB + rg * (G1_STAGE >> 4);
          if (tid == 0 && kb >= 6) TS(70 + kb);
          mbar_wait(bar + 8 * (B_FULL1 + rg), (kb / 3) & 1);
          if (tid == 0) TS(kb == 0 ? 1 : 46 + kb);
          wg_fence();
#pragma unroll
          for (int kk = 0; kk < REL; kk++) wgmma_ss<192, 0, 1>(acc0, da + 2 * kk, db + 64 * kk, (kb | kk) != 0);
          wg_commit();
          wg_wait<1>();
          if (kb > 0 && elect) mbar_arrive(bar + 8 * (B_EMPTY1 + kb % 3));
          wg_fence();
#pragma unroll
          for (int kk = REL; kk < 4; kk++) wgmma_ss<192, 0, 1>(acc0, da + 2 * kk, db + 64 * kk, 1);
#pragma unroll
          for (int kk = 0; kk < 4; kk++) wgmma_ss<192, 0, 1>(acc1, da + 512 + 2 * kk, db + 64 * kk, (kb | kk) != 0);
          wg_commit();
        }
        if (tid == 0) TS(78);
        mbar_wait(bar + 8 * (B_FULL1 + 0), 0);
        if (tid == 0) TS(59);
        wg_fence();
#pragma unroll
        for (int kk = 0; kk < REL; kk++) wgmma_ss<192, 0, 1>(acc0, dA + 2 * kk, dB + 64 * kk, 1);
        wg_commit();
        wg_wait<1>();
        if (elect) mbar_arrive(bar + 8 * B_R2FREE);
        wg_fence();
#pragma unroll
        for (int kk = REL; kk < 4; kk++) wgmma_ss<192, 0, 1>(acc0, dA + 2 * kk, dB + 64 * kk, 1);
        if (wg == 0) {
          wg_fence();
#pragma unroll
          for (int kk = 0; kk < 4; kk++) wgmma_ss<192, 0, 1>(acc1, dA + 512 + 2 * kk, dB + 64 * kk, 1);
        } else {
          bar_sync(2, 256);
        }
        if (tid == 0) TS(79);
        mbar_wait(bar + 8 * (B_FULL1 + 1), 1);
        if (tid == 0) TS(60);
        wg_fence();
#pragma unroll
        for (int kk = 0; kk < 4; kk++) wgmma_ss<192, 0, 1>(acc0, dA + (G1_STAGE >> 4) + 2 * kk, dB + (G1_STAGE >> 4) + 64 * kk, 1);
        wg_commit();
        if (wg == 1) {
          wg_fence();
#pragma unroll
          for (int kk = 0; kk < 4; kk++) wgmma_ss<192, 0, 1>(acc1, dA + 512 + 2 * kk, dB + 64 * kk, 1);
        }
        wg_fence();
#pragma unroll
        for (int kk = 0; kk < 4; kk++) wgmma_ss<192, 0, 1>(acc1, dA + (G1_STAGE >> 4) + 512 + 2 * kk, dB + (G1_STAGE >> 4) + 64 * kk, 1);
        wg_commit();
        bar_arrive(2 - wg, 256);
        const uint32_t hd = sb + (w >> 1) * G1_STAGE + wg * 16384 + (w & 1) * 3072 + (lane & 7) * 64 + (((lane >> 3) ^ ((lane & 7) >> 1)) << 4);
        wg_wait<1>();
        pin<96>(acc0);
        if (elect) TS(2 + wg);
        mbar_wait(bar + 8 * B_GATE, 0);
        glu_store(acc0, hd);
        asm volatile("fence.proxy.async.shared::cta;" ::: "memory");
        __syncwarp();
        if (lane == 0) mbar_arrive(bar + 8 * (B_SIGH + 2 * wg));
        if (wg == 0) {
          mbar_wait(bar + 8 * B_UFULL, 0);
          bar_sync(1, 256);
          if (elect) TS(10);
          conv_issue(d0, sb, 0);
          wg_commit();
          bar_arrive(2, 256);
          wg_wait<1>();
        } else {
          wg_wait<0>();
        }
        pin<96>(acc1);
        if (elect) { mbar_arrive(bar + 8 * B_G1DONE); TS(6 + wg); }
        glu_store(acc1, hd + 8192);
        asm volatile("fence.proxy.async.shared::cta;" ::: "memory");
        __syncwarp();
        if (lane == 0) mbar_arrive(bar + 8 * (B_SIGH + 2 * wg + 1));
        if (elect) TS(4 + wg);
      }
      wg_wait<0>();
      pin<64>(d0);
      if (wg == 0) {
        conv_finish(d0, sm, bar, 0, wg, w, lane);
        if (elect) TS(12);
      }
      const int ch = 3 - 2 * wg;
      mbar_wait(bar + 8 * (B_UFULL + ch), 0);
      bar_sync(1 + wg, 256);
      if (elect) TS(10 + 3 * ch);
      conv_issue(d0, sb, ch);
      wg_commit();
      mbar_wait(bar + 8 * (B_UFULL + ch + 1), 0);
      if (elect) TS(13 + 3 * ch);
      conv_issue(d1, sb, ch + 1);
      wg_commit();
      bar_arrive(2 - wg, 256);
      wg_wait<1>();
      pin<64>(d0);
      if (elect) TS(11 + 3 * ch);
      conv_finish(d0, sm, bar, ch, wg, w, lane);
      if (elect) TS(12 + 3 * ch);
      wg_wait<0>();
      pin<64>(d1);
      conv_finish(d1, sm, bar, ch + 1, wg, w, lane);
      if (elect) TS(15 + 3 * ch);
    }
    const int q = lane & 3, i8 = lane & 7, mi = lane >> 3;
    const uint32_t qa = sb + OFF_Q + ((mi >> 1) * 8 + i8) * 128 + (((2 * w + (mi & 1)) ^ i8) << 4);
    if (wg == 1) {
      float accF[80], accO[80];
      const uint64_t dA = mkdesc(sb, 1024, 1024, 1);
      const uint64_t dB = mkdesc(sb, 16, 512, 2);
      if (has1) bar_sync(2, 256);
#define G2_STAGE(S)                                                              \
      if (elect) TS(80 + 4 * r + S);                                             \
      mbar_wait(bar + 8 * (B_FULL2 + S), r);                                     \
      if (elect) TS(64 + 4 * r + S);                                             \
      wg_fence();                                                                \
      g2_half<S, 0, 0, REL2>(accF, dA, dB, (r | S) != 0);                        \
      wg_commit();                                                               \
      wg_wait<1>();                                                              \
      if ((r | S) != 0 && elect) mbar_arrive(bar + 8 * (B_EMPTY2 + ((S + 3) & 3))); \
      wg_fence();                                                                \
      g2_half<S, 0, REL2, 4>(accF, dA, dB, 1);                                   \
      g2_half<S, 1>(accO, dA, dB, (r | S) != 0);                                 \
      wg_commit();
#pragma unroll 1
      for (int r = 0; r < 2; r++) {
        G2_STAGE(0) G2_STAGE(1) G2_STAGE(2) G2_STAGE(3)
      }
      mbar_wait(bar + 8 * (B_FULL2 + 0), 0);
      if (elect) TS(72);
      wg_fence();
      g2_half<0, 0, 0, REL2>(accF, dA, dB, 1);
      wg_commit();
      wg_wait<1>();
      if (elect) mbar_arrive(bar + 8 * (B_EMPTY2 + 3));
      wg_fence();
      g2_half<0, 0, REL2, 4>(accF, dA, dB, 1);
      g2_half<0, 1>(accO, dA, dB, 1);
      mbar_wait(bar + 8 * (B_FULL2 + 1), 0);
      if (elect) TS(73);
      wg_fence();
      g2_half<1, 0>(accF, dA, dB, 1);
      mbar_wait(bar + 8 * (B_FULL2 + 2), 0);
      if (elect) TS(74);
      wg_fence();
      g2_half<2, 0>(accF, dA, dB, 1);
      mbar_wait(bar + 8 * (B_FULL2 + 3), 0);
      if (elect) TS(75);
      wg_fence();
      g2_half<3, 0>(accF, dA, dB, 1);
      wg_commit();
      g2_half<1, 1>(accO, dA, dB, 1);
      g2_half<2, 1>(accO, dA, dB, 1);
      g2_half<3, 1>(accO, dA, dB, 1);
      wg_commit();
      mbar_wait(bar + 8 * B_XF, 0);
      const uint32_t xo = OFF_XCH + (tid & 127) * 16;
      {
        const uint32_t xd = peer_addr(sb + xo), xb = peer_addr(bar + 8 * B_XCH);
        wg_wait<1>();
        pin<80>(accF);
        if (elect) TS(36);
#pragma unroll
        for (int i = 0; i < 10; i++)
          asm volatile("st.async.shared::cluster.mbarrier::complete_tx::bytes.v4.b32 [%0], {%1,%2,%3,%4}, [%5];" ::"r"(xd + i * 2048),
                       "r"(pack_bf16(accF[8 * i], accF[8 * i + 1])), "r"(pack_bf16(accF[8 * i + 2], accF[8 * i + 3])),
                       "r"(pack_bf16(accF[8 * i + 4], accF[8 * i + 5])), "r"(pack_bf16(accF[8 * i + 6], accF[8 * i + 7])), "r"(xb) : "memory");
      }
      if (elect) TS(37);
      bar_sync(6, 256);
      if (elect) TS(38);
      float om[40];
#pragma unroll
      for (int jp = 0; jp < 10; jp++) {
        uint32_t ga[4];
        asm volatile("ldmatrix.sync.aligned.m8n8.x4.trans.shared.b16 {%0,%1,%2,%3}, [%4];" : "=r"(ga[0]), "=r"(ga[1]), "=r"(ga[2]), "=r"(ga[3]) : "r"(qa + jp * 2048) : "memory");
#pragma unroll
        for (int m = 0; m < 4; m++) { accF[8 * jp + 2 * m] = bflo(ga[m]); accF[8 * jp + 2 * m + 1] = bfhi(ga[m]); }
      }
#pragma unroll
      for (int j = 0; j < 20; j++) {
        const float2 gt = *reinterpret_cast<const float2*>(sm + OFF_G + (j * 8 + 2 * q) * 4);
        om[2 * j] = 0.5f - 0.5f * gt.x;
        om[2 * j + 1] = 0.5f - 0.5f * gt.y;
      }
      mbar_wait(bar + 8 * B_XCH, 0);
      if (elect) TS(31);
#pragma unroll
      for (int i = 0; i < 10; i++) {
        const uint4 p = *reinterpret_cast<const uint4*>(sm + xo + i * 2048);
        const uint32_t pv[4] = {p.x, p.y, p.z, p.w};
#pragma unroll
        for (int m = 0; m < 4; m++) {
          const int j = 2 * i + (m >> 1);
          accF[8 * i + 2 * m] = fmaf(om[2 * j], bflo(pv[m]), accF[8 * i + 2 * m]);
          accF[8 * i + 2 * m + 1] = fmaf(om[2 * j + 1], bfhi(pv[m]), accF[8 * i + 2 * m + 1]);
        }
      }
      wg_wait<0>();
      pin<80>(accO);
      if (elect) TS(28);
#pragma unroll
      for (int hf = 0; hf < 2; hf++) {
#pragma unroll
        for (int jp = 5 * hf; jp < 5 * hf + 5; jp++) {
          uint32_t ov[4];
#pragma unroll
          for (int m = 0; m < 4; m++) {
            const int j = 2 * jp + (m >> 1), i = 8 * jp + 2 * m;
            ov[m] = pack_bf16(fmaf(om[2 * j], accO[i], accF[i]), fmaf(om[2 * j + 1], accO[i + 1], accF[i + 1]));
          }
          asm volatile("stmatrix.sync.aligned.m8n8.x4.trans.shared.b16 [%0], {%1,%2,%3,%4};" ::"r"(qa + jp * 2048), "r"(ov[0]), "r"(ov[1]), "r"(ov[2]), "r"(ov[3]) : "memory");
        }
        asm volatile("fence.proxy.async.shared::cta;" ::: "memory");
        bar_sync(4, 128);
        if (elect) tma4_store(&mO, sb + OFF_Q + hf * 10240, db * 64, 0, ((2 * tb + hf) % 13) * 10, (2 * tb + hf) / 13);
      }
      if (elect) {
        asm volatile("cp.async.bulk.commit_group;" ::: "memory");
        asm volatile("cp.async.bulk.wait_group.read 0;" ::: "memory");
        TS(30);
      }
    } else {
      mbar_wait(bar + 8 * B_QZ, 0);
      if (elect) TS(27);
      uint32_t qv[40], zv[40], g2[20];
      const uint32_t za = sb + OFF_Z + (16 * w + 8 * (mi & 1) + i8) * 160 + (mi >> 1) * 16;
#pragma unroll
      for (int jp = 0; jp < 10; jp++) {
        asm volatile("ldmatrix.sync.aligned.m8n8.x4.trans.shared.b16 {%0,%1,%2,%3}, [%4];" : "=r"(qv[4 * jp]), "=r"(qv[4 * jp + 1]), "=r"(qv[4 * jp + 2]), "=r"(qv[4 * jp + 3]) : "r"(qa + jp * 2048) : "memory");
        asm volatile("ldmatrix.sync.aligned.m8n8.x4.shared.b16 {%0,%1,%2,%3}, [%4];" : "=r"(zv[4 * jp]), "=r"(zv[4 * jp + 1]), "=r"(zv[4 * jp + 2]), "=r"(zv[4 * jp + 3]) : "r"(za + (jp / 5) * 10240 + (jp % 5) * 32) : "memory");
      }
#pragma unroll
      for (int j = 0; j < 20; j++) {
        const float2 gt = *reinterpret_cast<const float2*>(sm + OFF_G + (j * 8 + 2 * q) * 4);
        g2[j] = pack_bf16(gt.x, gt.y);
      }
#pragma unroll
      for (int jp = 0; jp < 10; jp++) {
#pragma unroll
        for (int m = 0; m < 4; m++) qv[4 * jp + m] = bmul2(bmul2(qv[4 * jp + m], zv[4 * jp + m]), g2[2 * jp + (m >> 1)]);
        asm volatile("stmatrix.sync.aligned.m8n8.x4.trans.shared.b16 [%0], {%1,%2,%3,%4};" ::"r"(qa + jp * 2048), "r"(qv[4 * jp]), "r"(qv[4 * jp + 1]), "r"(qv[4 * jp + 2]), "r"(qv[4 * jp + 3]) : "memory");
      }
      bar_arrive(6, 256);
      if (elect) TS(29);
    }
  } else {
    asm volatile("setmaxnreg.dec.sync.aligned.u32 56;");
    if (warp == 8) {
      if (has1) {
        if (lane == 0) {
          tma3(sb + OFF_H, &mK, (cta & 7) * 80, (cta >> 3) * 16 - 2, 0, bar + 8 * B_KV);
          tma3(sb + OFF_V, &mV, (cta & 7) * 80, (cta >> 3) * 16 - 1, 0, bar + 8 * B_KV);
          bulk_g2s(sb + OFF_EX, P.shift_k + (cta & 7) * 320, 640, bar + 8 * B_KV);
        }
        float s[4] = {0.f, 0.f, 0.f, 0.f};
        const uint32_t xa = sb + ft * 2048 + (lane >> 3) * 128;
#pragma unroll 1
        for (int kb = 2; kb < 12; kb++) {
          if (lane == 0 && kb >= 3 && kb < 10) {
            const int rg = (kb + 1) % 3;
            const uint32_t dst = sb + rg * G1_STAGE, fb = bar + 8 * (B_FULL1 + rg);
            mbar_wait_t(bar + 8 * (B_EMPTY1 + rg), (kb / 3 - 1) & 1);
            TS(85 + kb);
            mbar_expect(fb, G1_STAGE);
            tma4(dst, &mX, kb * 64, 0, (mb & 3) * 32, mb >> 2, fb);
            tma3(dst + 32768, &mWg, 0, kb * 64, ft * 3, fb);
            tma3(dst + 32768 + 12288, &mWu, 0, kb * 64, ft * 3, fb);
            if (kb == PFK) bulk_prefetch(P.ssm_k + (size_t)cta * 5 * 2048, 20480);
            if (kb == PFW) bulk_prefetch(P.w_down + (size_t)cta * 7680, 15360);
          }
          __syncwarp();
          const int kg = kb - 2, rg = (kb - 1) % 3;
          mbar_wait_t(bar + 8 * (B_FULL1 + rg), (kg / 3) & 1);
          uint4 xv[4], gw;
#pragma unroll
          for (int i = 0; i < 4; i++)
            asm volatile("ld.shared.v4.u32 {%0,%1,%2,%3}, [%4];" : "=r"(xv[i].x), "=r"(xv[i].y), "=r"(xv[i].z), "=r"(xv[i].w)
                         : "r"(xa + rg * G1_STAGE + i * 512 + (((lane & 7) ^ ((lane >> 3) + 4 * (i & 1))) << 4)) : "memory");
          asm volatile("ld.shared.v4.u32 {%0,%1,%2,%3}, [%4];" : "=r"(gw.x), "=r"(gw.y), "=r"(gw.z), "=r"(gw.w) : "r"(sb + OFF_EX + 640 + kg * 128 + (lane & 7) * 16) : "memory");
#pragma unroll
          for (int i = 0; i < 4; i++) {
            const uint32_t p0 = bmul2(xv[i].x, gw.x), p1 = bmul2(xv[i].y, gw.y), p2 = bmul2(xv[i].z, gw.z), p3 = bmul2(xv[i].w, gw.w);
            s[i] += (bflo(p0) + bfhi(p0)) + (bflo(p1) + bfhi(p1)) + ((bflo(p2) + bfhi(p2)) + (bflo(p3) + bfhi(p3)));
          }
          __syncwarp();
          if (kg == 7 && lane == 0) mbar_arrive(bar + 8 * B_R2FREE);
        }
        if (lane == 0) { mbar_arrive(bar + 8 * B_GATE); TS(44); }
        float s0 = (lane & 4) ? s[2] : s[0], s1 = (lane & 4) ? s[3] : s[1];
        s0 += __shfl_xor_sync(0xffffffffu, (lane & 4) ? s[0] : s[2], 4);
        s1 += __shfl_xor_sync(0xffffffffu, (lane & 4) ? s[1] : s[3], 4);
        float sv = (lane & 2) ? s1 : s0;
        sv += __shfl_xor_sync(0xffffffffu, (lane & 2) ? s0 : s1, 2);
        sv += __shfl_xor_sync(0xffffffffu, sv, 1);
        sv = __bfloat162float(__float2bfloat16(sv));
        reinterpret_cast<float*>(sm + OFF_GS)[(lane & 6) * 2 + (lane >> 3)] = __bfloat162float(__float2bfloat16(1.f / (1.f + __expf(-sv))));
        asm volatile("fence.proxy.async.shared::cta;" ::: "memory");
        __syncwarp();
      }
      if (lane == 0) {
        if (has1) {
          mbar_arrive(bar + 8 * B_GS);
          mbar_wait_t(bar + 8 * B_R2FREE, 0);
        }
#pragma unroll 1
        for (int it = 0; it < 12; it++) {
          const uint32_t fb = bar + 8 * (B_FULL2 + (it & 3));
          if (it >= 4) mbar_wait_t(bar + 8 * (B_EMPTY2 + (it & 3)), (it >> 3) & 1);
          else if (it == 1 && has1) mbar_wait_t(bar + 8 * B_G1DONE, 0);
          TS(96 + it);
          mbar_expect(fb, 36864);
          tma3(sb + slotF(it & 3), &mWd, 0, rank * 768 + it * 64, db ^ 1, fb);
          tma3(sb + slotO(it & 3), &mWd, 0, rank * 768 + it * 64, db, fb);
        }
      }
    } else {
      const int hw = warp - 9;
      if (hw == 2) asm volatile("barrier.cluster.arrive.release.aligned;\nbarrier.cluster.wait.acquire.aligned;" ::: "memory");
      if (has1) {
      {
        const int cq = lane & 3, gl = hw < 2 ? hw * 8 + (lane >> 2) + 1 : 0;
        const bool act = hw < 2 || lane < 4;
        const uint32_t kp = sb + OFF_H + gl * 160 + cq * 8;
        const uint32_t u1 = sb + OFF_US + cq * 2048 + (15 - gl) * 16, u2 = u1 + 24;
        const uint32_t ua = (cq & 1) ? u2 : u1, ub = (cq & 1) ? u1 : u2;
        const bool pa = act && ((cq & 1) ? gl >= 1 : gl <= 15), pb = act && ((cq & 1) ? gl <= 15 : gl >= 1);
        mbar_wait_t(bar + 8 * B_KV, 0);
        if (hw == 0 && lane == 0) TS(39);
#pragma unroll 1
        for (int cb = 0; cb < 5; cb++) {
          uint2 vr[8];
          if (act) {
            uint2 kr[11];
#pragma unroll
            for (int r = 0; r < 3; r++) kr[r] = lds64(kp + cb * 32 + (r + 5) * 18 * 160);
#pragma unroll
            for (int r = 0; r < 8; r++) kr[r + 3] = lds64(kp + cb * 32 + (r * 18 + 1) * 160);
#pragma unroll
            for (int r = 0; r < 8; r++) vr[r] = lds64(kp + cb * 32 + 23040 + r * 17 * 160);
            uint4 sa, sc;
            asm volatile("ld.volatile.shared.v4.u32 {%0,%1,%2,%3}, [%4];" : "=r"(sa.x), "=r"(sa.y), "=r"(sa.z), "=r"(sa.w) : "r"(sb + OFF_EX + cb * 128 + cq * 32) : "memory");
            asm volatile("ld.volatile.shared.v4.u32 {%0,%1,%2,%3}, [%4];" : "=r"(sc.x), "=r"(sc.y), "=r"(sc.z), "=r"(sc.w) : "r"(sb + OFF_EX + cb * 128 + cq * 32 + 16) : "memory");
            const uint32_t wa[4] = {__byte_perm(sa.x, sa.z, 0x5410), __byte_perm(sa.x, sa.z, 0x7632), __byte_perm(sa.y, sa.w, 0x5410), __byte_perm(sa.y, sa.w, 0x7632)};
            const uint32_t wb[4] = {__byte_perm(sc.x, sc.z, 0x5410), __byte_perm(sc.x, sc.z, 0x7632), __byte_perm(sc.y, sc.w, 0x5410), __byte_perm(sc.y, sc.w, 0x7632)};
#pragma unroll
            for (int r = 0; r < 8; r++) {
              uint32_t x = bmul2(kr[r].x, wa[3]), y = bmul2(kr[r].y, wb[3]);
#pragma unroll
              for (int j = 1; j < 4; j++) {
                x = bfma2(kr[r + j].x, wa[3 - j], x);
                y = bfma2(kr[r + j].y, wb[3 - j], y);
              }
              vr[r].x = bmul2(x, vr[r].x);
              vr[r].y = bmul2(y, vr[r].y);
            }
          }
          if (hw == 2 && lane == 0) asm volatile("cp.async.bulk.wait_group.read 0;" ::: "memory");
          __syncwarp();
          bar_sync(5, 96);
          if (cb == 4 && hw == 1 && lane == 0) {
            mbar_expect(bar + 8 * B_HLD, 20480);
            for (int ch = 0; ch < 5; ch++)
              bulk_g2s(sb + OFF_H + (2 * ch + 1) * H_PITCH + 224, P.ssm_k + (size_t)(cta * 5 + ch) * 2048, 4096, bar + 8 * B_HLD);
          }
#pragma unroll
          for (int cc = 0; cc < 4; cc++) {
            const uint32_t sel = (cc & 1) ? 0x7632 : 0x5410;
#pragma unroll
            for (int p = 0; p < 2; p++) {
              const int r = 4 - 4 * p;
              const uint32_t qx = (cc & 2) ? __byte_perm(vr[r].y, vr[r + 1].y, sel) : __byte_perm(vr[r].x, vr[r + 1].x, sel);
              const uint32_t qy = (cc & 2) ? __byte_perm(vr[r + 2].y, vr[r + 3].y, sel) : __byte_perm(vr[r + 2].x, vr[r + 3].x, sel);
              if (pa) asm volatile("st.shared.v2.u32 [%0], {%1,%2};" ::"r"(ua + cc * 512 + p * 256), "r"(qx), "r"(qy) : "memory");
              if (pb) asm volatile("st.shared.v2.u32 [%0], {%1,%2};" ::"r"(ub + cc * 512 + p * 256), "r"(qx), "r"(qy) : "memory");
            }
          }
          asm volatile("fence.proxy.async.shared::cta;" ::: "memory");
          __syncwarp();
          bar_sync(5, 96);
          if (hw == 2 && lane == 0) {
            tma2_store(&mU, sb + OFF_US, 1920 - 128 * (cta >> 3), (cta & 7) * 160 + cb * 32);
            asm volatile("cp.async.bulk.commit_group;" ::: "memory");
          }
        }
        if (lane == 0) TS(54 + hw);
        if (hw == 2 && lane == 0) {
          asm volatile("cp.async.bulk.wait_group 0;" ::: "memory");
          flag_add(&g_cnt[(C_U + (cta & 7)) * 32]);
          TS(40);
          flag_wait(&g_cnt[(C_U + mb) * 32], &g_cnt[(C_U + mb) * 32], 16);
          TS(32);
          mbar_wait_t(bar + 8 * B_R2FREE, 0);
#pragma unroll 1
          for (int ch = 0; ch < 5; ch++) {
            mbar_expect(bar + 8 * (B_UFULL + ch), 8192);
            bulk_g2s(sb + OFF_U + (4 - ch) * 8192, g_U + (size_t)(5 * cta + ch) * 4096, 8192, bar + 8 * (B_UFULL + ch));
          }
          TS(33);
        }
      }
      if (hw < 2) {
        const int ht = tid - 288;
        for (int i = ht; i < 10 * 15; i += 64) {
          const int b = i / 15, e = i % 15;
          if (e < 14) *reinterpret_cast<uint4*>(sm + OFF_H + b * H_PITCH + e * 16) = make_uint4(0u, 0u, 0u, 0u);
          else if ((b & 1) == 0) *reinterpret_cast<uint2*>(sm + OFF_H + b * H_PITCH + 224) = make_uint2(0u, 0u);
        }
        const float dv = lane < 5 ? __bfloat162float(P.ssm_D[cta * 5 + lane]) : 0.f;
        mbar_wait_t(bar + 8 * B_HLD, 0);
        if (hw == 0) {
          if (lane < 5) {
            __nv_bfloat16* h0 = reinterpret_cast<__nv_bfloat16*>(sm + OFF_H + (2 * lane + 1) * H_PITCH + 224);
            *h0 = __float2bfloat16(__bfloat162float(*h0) + dv);
          }
          __syncwarp();
        }
#pragma unroll 1
        for (int b = 0; b < 5; b++) {
          unsigned char* dst = sm + OFF_H + b * 2 * H_PITCH + hw * 2048 + 232 + lane * 8;
          uint2 hv[8];
#pragma unroll
          for (int u = 0; u < 8; u++) hv[u] = *reinterpret_cast<const uint2*>(dst + H_PITCH - 8 + u * 256);
#pragma unroll
          for (int u = 0; u < 8; u++) *reinterpret_cast<uint2*>(dst + u * 256) = hv[u];
          asm volatile("fence.proxy.async.shared::cta;" ::: "memory");
          __syncwarp();
          if (lane == 0) mbar_arrive(bar + 8 * (B_UFULL + b));
        }
        if (hw == 1 && lane == 0) TS(41);
      }
      }
      if (lane == 0) {
        if (hw == 0) {
          const int ga = 20 * tb, gb = ga + 19;
          const unsigned* fa = &g_cnt[(C_H + 2 * ((ga / 130) * 4 + min((ga % 130) >> 5, 3))) * 32];
          const unsigned* fb = &g_cnt[(C_H + 2 * ((gb / 130) * 4 + min((gb % 130) >> 5, 3))) * 32];
          flag_wait(fa + rank * 32, fb + rank * 32, 8);
          TS(34);
          const __nv_bfloat16* hsrc = g_Hs + (size_t)(rank * 24 * NGRP + ga) * 256;
          if (has1) mbar_wait_t(bar + 8 * B_HDR, 0);
#pragma unroll 1
          for (int it = 0; it < 12; it++) {
            if (it >= 4) mbar_wait_t(bar + 8 * (B_EMPTY2 + (it & 3)), (it >> 3) & 1);
            else if (it == 3 && has1) { mbar_wait_t(bar + 8 * (B_CD + 0), 0); mbar_wait_t(bar + 8 * (B_CD + 1), 0); }
            TS(112 + it);
            bulk_g2s(sb + slotB0(it & 3), hsrc + (size_t)it * (2 * NGRP * 256), 10240, bar + 8 * (B_FULL2 + (it & 3)));
            bulk_g2s(sb + slotB1(it & 3), hsrc + (size_t)it * (2 * NGRP * 256) + NGRP * 256, 10240, bar + 8 * (B_FULL2 + (it & 3)));
            if (it == 3) {
              flag_wait(fa + (rank ^ 1) * 32, fb + (rank ^ 1) * 32, 8);
              bulk_g2s(sb + OFF_G, g_gate + ga * 8, 640, bar + 8 * B_QZ);
            }
          }
        } else if (hw == 1) {
          prefetch_map(&mQ); prefetch_map(&mZ); prefetch_map(&mO);
          if (has1) for (int ch = 0; ch < 3; ch++) mbar_wait_t(bar + 8 * (B_CD + ch), 0);
          mbar_expect(bar + 8 * B_QZ, 40960 + 640);
          for (int hf = 0; hf < 2; hf++)
            tma4(sb + OFF_Q + hf * 10240, &mQ, db * 64, 0, ((2 * tb + hf) % 13) * 10, (2 * tb + hf) / 13, bar + 8 * B_QZ);
          if (has1) { mbar_wait_t(bar + 8 * (B_CD + 3), 0); mbar_wait_t(bar + 8 * (B_CD + 4), 0); }
          flag_wait(&g_cnt[(C_Z + db) * 32], &g_cnt[(C_Z + db) * 32], (64 * db + 63) / 5 - (64 * db) / 5 + 1);
          TS(35);
          tma3(sb + OFF_Z, &mZ, 0, db * 64, 2 * tb, bar + 8 * B_QZ);
          mbar_wait_t(bar + 8 * B_QZ, 0);
          if (atomicAdd(&g_cnt[C_DONE * 32], 1u) == NCTA - 1) {
            for (int i = 0; i < C_COUNT; i++) g_cnt[i * 32] = 0;
          }
        } else {
          if (has1) {
            const int g0 = (mb >> 2) * 130 + (mb & 3) * 32;
            mbar_wait_t(bar + 8 * B_GS, 0);
            bulk_s2g(g_gate + (g0 + 2 * ft) * 8, sb + OFF_GS, 64);
#pragma unroll 1
            for (int j = 0; j < 4; j++) {
              const int i = j == 3 ? 1 : j == 0 ? 0 : j + 1;
              mbar_wait_t(bar + 8 * (B_SIGH + i), 0);
              tma3_store(&mH, sb + i * 8192, 0, 3 * ft, g0 + 8 * i);
              tma3_store(&mH, sb + G1_STAGE + i * 8192, 0, 3 * ft, g0 + 8 * i + 4);
            }
            asm volatile("cp.async.bulk.commit_group;" ::: "memory");
            asm volatile("cp.async.bulk.wait_group.read 0;" ::: "memory");
            mbar_arrive(bar + 8 * B_HDR);
            TS(45);
            asm volatile("cp.async.bulk.wait_group 0;" ::: "memory");
            TS(57);
            flag_add(&g_cnt[(C_H + 2 * mb + (ft >> 3)) * 32]);
            TS(42);
#pragma unroll 1
            for (int ch = 0; ch < 5; ch++) {
              __nv_bfloat16* zd = g_zT + (size_t)(5 * cta + ch) * (NGRP * 8);
              mbar_wait_t(bar + 8 * (B_SIGZ + ch), 0);
              bulk_s2g(zd, sb + zstage(ch), 2048);
              bulk_s2g(zd + 130 * 8, sb + zstage(ch) + 2048, 2048);
            }
            TS(58);
            asm volatile("cp.async.bulk.commit_group;" ::: "memory");
            asm volatile("cp.async.bulk.wait_group 0;" ::: "memory");
            flag_add(&g_cnt[(C_Z + (5 * cta) / 64) * 32]);
            if ((5 * cta) / 64 != (5 * cta + 4) / 64) flag_add(&g_cnt[(C_Z + (5 * cta + 4) / 64) * 32]);
            TS(43);
          }
          asm volatile("mbarrier.arrive.relaxed.cluster.shared::cluster.b64 _, [%0];" ::"r"(peer_addr(bar + 8 * B_XF)) : "memory");
        }
      }
    }
  }
}

typedef CUresult (*EncFn)(CUtensorMap*, CUtensorMapDataType, cuuint32_t, void*, const cuuint64_t*, const cuuint64_t*,
                          const cuuint32_t*, const cuuint32_t*, CUtensorMapInterleave, CUtensorMapSwizzle,
                          CUtensorMapL2promotion, CUtensorMapFloatOOBfill);

void make_map(EncFn enc, CUtensorMap* m, const void* ptr, int rank, const cuuint64_t* dims, const cuuint64_t* str,
              const cuuint32_t* box, CUtensorMapSwizzle sw) {
  const cuuint32_t es[5] = {1, 1, 1, 1, 1};
  enc(m, CU_TENSOR_MAP_DATA_TYPE_BFLOAT16, rank, const_cast<void*>(ptr), dims, str, box, es, CU_TENSOR_MAP_INTERLEAVE_NONE,
      sw, CU_TENSOR_MAP_L2_PROMOTION_L2_128B, CU_TENSOR_MAP_FLOAT_OOB_FILL_NONE);
}

__global__ void probe_kernel() {}

void cluster_order(unsigned char* perm) {
  constexpr int NP = NCTA / 2;
  for (int c = 0; c < NP; c++) perm[c] = c;
  int n[9] = {0};
  cudaFuncSetAttribute(probe_kernel, cudaFuncAttributeMaxDynamicSharedMemorySize, SMEM_BYTES);
  cudaFuncSetAttribute(probe_kernel, cudaFuncAttributeNonPortableClusterSizeAllowed, 1);
  for (int k = 1; k <= 8; k++) {
    cudaLaunchConfig_t cfg = {};
    cudaLaunchAttribute at;
    at.id = cudaLaunchAttributeClusterDimension;
    at.val.clusterDim.x = 2 * k; at.val.clusterDim.y = 1; at.val.clusterDim.z = 1;
    cfg.gridDim = dim3(16 * k); cfg.blockDim = dim3(384); cfg.dynamicSmemBytes = SMEM_BYTES;
    cfg.attrs = &at; cfg.numAttrs = 1;
    if (cudaOccupancyMaxActiveClusters(&n[k], probe_kernel, &cfg) != cudaSuccess) { cudaGetLastError(); return; }
  }
  int R[9];
  R[7] = n[8]; R[6] = n[7]; R[5] = n[6]; R[4] = n[5]; R[3] = n[4] - n[8];
  R[0] = R[1] = R[2] = n[2] - R[3] - R[5] - R[7];
  R[8] = n[3] - R[2] - R[5];
  int lone = n[1];
  for (int r = 0; r < 9; r++) {
    if (R[r] < 0 || R[r] > 16 || (r && R[r] > R[r - 1])) return;
    lone -= R[r];
  }
  if (lone < 0 || n[1] < NP) return;
  int gpc[NP], rnd[NP];
  for (int c = 0, r = 0, pos = 0; c < NP; c++) {
    if (c < lone) { gpc[c] = -1; rnd[c] = 8; continue; }
    while (pos >= R[r]) { pos = 0; r++; }
    gpc[c] = R[0] - R[r] + pos++; rnd[c] = r;
  }
  int m = 0;
  for (int g = R[0] - 1; g >= 0; g--)
    for (int c = 0; c < NP; c++) if (gpc[c] == g && rnd[c] < 8) perm[c] = m++;
  for (int c = NP - 1; c >= 0; c--) if (rnd[c] == 8) perm[c] = m++;
}

}

extern "C" void kernel_launch(void* const* d_in, const int* in_sizes, int n_in, void* d_out, int out_size) {
  (void)in_sizes; (void)n_in; (void)out_size;
  static EncFn enc = nullptr;
  static unsigned char perm[NCTA / 2];
  static void *zT = nullptr, *uT = nullptr, *hT = nullptr;
  if (!enc) {
    cudaDriverEntryPointQueryResult qr;
    cudaGetDriverEntryPoint("cuTensorMapEncodeTiled", (void**)&enc, cudaEnableDefault, &qr);
    cudaGetSymbolAddress(&zT, g_zT);
    cudaGetSymbolAddress(&uT, g_U);
    cudaGetSymbolAddress(&hT, g_Hs);
    cudaFuncSetAttribute(fused_kernel, cudaFuncAttributeMaxDynamicSharedMemorySize, SMEM_BYTES);
    cluster_order(perm);
  }
  CUtensorMap mX, mWg, mWu, mWd, mQ, mZ, mO, mK, mV, mU, mH;
  {
    const cuuint64_t dims[4] = {640, 8, 128, 2}, str[3] = {128 * 1280, 1280, 1024 * 1280};
    const cuuint32_t b1[4] = {64, 8, 32, 1}, b2[4] = {64, 8, 10, 1};
    make_map(enc, &mX, d_in[0], 4, dims, str, b1, CU_TENSOR_MAP_SWIZZLE_128B);
    make_map(enc, &mQ, d_in[0], 4, dims, str, b2, CU_TENSOR_MAP_SWIZZLE_128B);
    make_map(enc, &mO, d_out, 4, dims, str, b2, CU_TENSOR_MAP_SWIZZLE_128B);
  }
  {
    const cuuint64_t dims[3] = {32, 640, 48}, str[2] = {3072, 64};
    const cuuint32_t box[3] = {32, 64, 3};
    make_map(enc, &mWg, d_in[7], 3, dims, str, box, CU_TENSOR_MAP_SWIZZLE_64B);
    make_map(enc, &mWu, d_in[8], 3, dims, str, box, CU_TENSOR_MAP_SWIZZLE_64B);
  }
  {
    const cuuint64_t dims[3] = {64, 1536, 10}, str[2] = {1280, 128};
    const cuuint32_t box[3] = {64, 64, 1};
    make_map(enc, &mWd, d_in[9], 3, dims, str, box, CU_TENSOR_MAP_SWIZZLE_128B);
  }
  {
    const cuuint64_t dims[3] = {80, 640, 26}, str[2] = {NGRP * 16, 160};
    const cuuint32_t box[3] = {80, 64, 2};
    make_map(enc, &mZ, zT, 3, dims, str, box, CU_TENSOR_MAP_SWIZZLE_NONE);
  }
  {
    const cuuint64_t dims[3] = {256, 48, NGRP}, str[2] = {NGRP * 512, 512};
    const cuuint32_t box[3] = {256, 3, 4};
    make_map(enc, &mH, hT, 3, dims, str, box, CU_TENSOR_MAP_SWIZZLE_NONE);
  }
  {
    const cuuint64_t dims[3] = {640, 256, 8}, str[2] = {8 * 1280, 1280};
    const cuuint32_t bk[3] = {80, 18, 8}, bv[3] = {80, 17, 8};
    make_map(enc, &mK, d_in[1], 3, dims, str, bk, CU_TENSOR_MAP_SWIZZLE_NONE);
    make_map(enc, &mV, d_in[2], 3, dims, str, bv, CU_TENSOR_MAP_SWIZZLE_NONE);
  }
  {
    const cuuint64_t dims[2] = {2048, 1280}, str[1] = {4096};
    const cuuint32_t box[2] = {128, 32};
    make_map(enc, &mU, uT, 2, dims, str, box, CU_TENSOR_MAP_SWIZZLE_NONE);
  }
  Params P;
  P.q = (const __nv_bfloat16*)d_in[0]; P.k = (const __nv_bfloat16*)d_in[1]; P.v = (const __nv_bfloat16*)d_in[2];
  P.w_gate = (const __nv_bfloat16*)d_in[7]; P.w_up = (const __nv_bfloat16*)d_in[8]; P.w_down = (const __nv_bfloat16*)d_in[9];
  P.shift_k = (const __nv_bfloat16*)d_in[3]; P.ssm_k = (const __nv_bfloat16*)d_in[4]; P.ssm_D = (const __nv_bfloat16*)d_in[5];
  P.gate_w = (const __nv_bfloat16*)d_in[10];
  for (int c = 0; c < 65; c++) P.perm[c] = perm[c];
  fused_kernel<<<NCTA, 384, SMEM_BYTES>>>(mX, mWg, mWu, mWd, mQ, mZ, mO, mK, mV, mU, mH, P);
}
```

```cpp
#include <cuda_runtime.h>
#include <cuda.h>
#include <cuda_bf16.h>
#include <stdint.h>

namespace {
#define TM9 4
#define TM10 4
#define GMAP 1
#define G1MAP 1
#define REL 2
#define TLA 2
#define CV0 3
#define CV4S 0
#define CV4 0, 4, 8, 12, 16, 22, 26, 29
#define GL1S 0
#define GL1 0, 2, 4, 6, 8, 11, 14
#define G1SB sb
#define KVAT 0
#define KVPF 2
#define KVA 1
#define KVB 2
#define REL2 3
#define PFK 4
#define PFW 6

template<int TA, int TB> __device__ __forceinline__ void wgmma_n8(float* d, uint64_t da, uint64_t db, int sc) {
  asm volatile("{\n.reg .pred p;\nsetp.ne.b32 p, %6, 0;\n"
    "wgmma.mma_async.sync.aligned.m64n8k16.f32.bf16.bf16 {%0, %1, %2, %3}, %4, %5, p, 1, 1, %7, %8;\n}\n"
    : "+f"(d[0]), "+f"(d[1]), "+f"(d[2]), "+f"(d[3])
    : "l"(da), "l"(db), "r"(sc), "n"(TA), "n"(TB));
}
template<int TA, int TB> __device__ __forceinline__ void wgmma_n16(float* d, uint64_t da, uint64_t db, int sc) {
  asm volatile("{\n.reg .pred p;\nsetp.ne.b32 p, %10, 0;\n"
    "wgmma.mma_async.sync.aligned.m64n16k16.f32.bf16.bf16 {%0, %1, %2, %3, %4, %5, %6, %7}, %8, %9, p, 1, 1, %11, %12;\n}\n"
    : "+f"(d[0]), "+f"(d[1]), "+f"(d[2]), "+f"(d[3]), "+f"(d[4]), "+f"(d[5]), "+f"(d[6]), "+f"(d[7])
    : "l"(da), "l"(db), "r"(sc), "n"(TA), "n"(TB));
}
template<int TA, int TB> __device__ __forceinline__ void wgmma_n24(float* d, uint64_t da, uint64_t db, int sc) {
  asm volatile("{\n.reg .pred p;\nsetp.ne.b32 p, %14, 0;\n"
    "wgmma.mma_async.sync.aligned.m64n24k16.f32.bf16.bf16 {%0, %1, %2, %3, %4, %5, %6, %7, %8, %9, %10, %11}, %12, %13, p, 1, 1, %15, %16;\n}\n"
    : "+f"(d[0]), "+f"(d[1]), "+f"(d[2]), "+f"(d[3]), "+f"(d[4]), "+f"(d[5]), "+f"(d[6]), "+f"(d[7]), "+f"(d[8]), "+f"(d[9]), "+f"(d[10]), "+f"(d[11])
    : "l"(da), "l"(db), "r"(sc), "n"(TA), "n"(TB));
}
template<int TA, int TB> __device__ __forceinline__ void wgmma_n32(float* d, uint64_t da, uint64_t db, int sc) {
  asm volatile("{\n.reg .pred p;\nsetp.ne.b32 p, %18, 0;\n"
    "wgmma.mma_async.sync.aligned.m64n32k16.f32.bf16.bf16 {%0, %1, %2, %3, %4, %5, %6, %7, %8, %9, %10, %11, %12, %13, %14, %15}, %16, %17, p, 1, 1, %19, %20;\n}\n"
    : "+f"(d[0]), "+f"(d[1]), "+f"(d[2]), "+f"(d[3]), "+f"(d[4]), "+f"(d[5]), "+f"(d[6]), "+f"(d[7]), "+f"(d[8]), "+f"(d[9]), "+f"(d[10]), "+f"(d[11]), "+f"(d[12]), "+f"(d[13]), "+f"(d[14]), "+f"(d[15])
    : "l"(da), "l"(db), "r"(sc), "n"(TA), "n"(TB));
}
template<int TA, int TB> __device__ __forceinline__ void wgmma_n40(float* d, uint64_t da, uint64_t db, int sc) {
  asm volatile("{\n.reg .pred p;\nsetp.ne.b32 p, %22, 0;\n"
    "wgmma.mma_async.sync.aligned.m64n40k16.f32.bf16.bf16 {%0, %1, %2, %3, %4, %5, %6, %7, %8, %9, %10, %11, %12, %13, %14, %15, %16, %17, %18, %19}, %20, %21, p, 1, 1, %23, %24;\n}\n"
    : "+f"(d[0]), "+f"(d[1]), "+f"(d[2]), "+f"(d[3]), "+f"(d[4]), "+f"(d[5]), "+f"(d[6]), "+f"(d[7]), "+f"(d[8]), "+f"(d[9]), "+f"(d[10]), "+f"(d[11]), "+f"(d[12]), "+f"(d[13]), "+f"(d[14]), "+f"(d[15]), "+f"(d[16]), "+f"(d[17]), "+f"(d[18]), "+f"(d[19])
    : "l"(da), "l"(db), "r"(sc), "n"(TA), "n"(TB));
}
template<int TA, int TB> __device__ __forceinline__ void wgmma_n48(float* d, uint64_t da, uint64_t db, int sc) {
  asm volatile("{\n.reg .pred p;\nsetp.ne.b32 p, %26, 0;\n"
    "wgmma.mma_async.sync.aligned.m64n48k16.f32.bf16.bf16 {%0, %1, %2, %3, %4, %5, %6, %7, %8, %9, %10, %11, %12, %13, %14, %15, %16, %17, %18, %19, %20, %21, %22, %23}, %24, %25, p, 1, 1, %27, %28;\n}\n"
    : "+f"(d[0]), "+f"(d[1]), "+f"(d[2]), "+f"(d[3]), "+f"(d[4]), "+f"(d[5]), "+f"(d[6]), "+f"(d[7]), "+f"(d[8]), "+f"(d[9]), "+f"(d[10]), "+f"(d[11]), "+f"(d[12]), "+f"(d[13]), "+f"(d[14]), "+f"(d[15]), "+f"(d[16]), "+f"(d[17]), "+f"(d[18]), "+f"(d[19]), "+f"(d[20]), "+f"(d[21]), "+f"(d[22]), "+f"(d[23])
    : "l"(da), "l"(db), "r"(sc), "n"(TA), "n"(TB));
}
template<int TA, int TB> __device__ __forceinline__ void wgmma_n56(float* d, uint64_t da, uint64_t db, int sc) {
  asm volatile("{\n.reg .pred p;\nsetp.ne.b32 p, %30, 0;\n"
    "wgmma.mma_async.sync.aligned.m64n56k16.f32.bf16.bf16 {%0, %1, %2, %3, %4, %5, %6, %7, %8, %9, %10, %11, %12, %13, %14, %15, %16, %17, %18, %19, %20, %21, %22, %23, %24, %25, %26, %27}, %28, %29, p, 1, 1, %31, %32;\n}\n"
    : "+f"(d[0]), "+f"(d[1]), "+f"(d[2]), "+f"(d[3]), "+f"(d[4]), "+f"(d[5]), "+f"(d[6]), "+f"(d[7]), "+f"(d[8]), "+f"(d[9]), "+f"(d[10]), "+f"(d[11]), "+f"(d[12]), "+f"(d[13]), "+f"(d[14]), "+f"(d[15]), "+f"(d[16]), "+f"(d[17]), "+f"(d[18]), "+f"(d[19]), "+f"(d[20]), "+f"(d[21]), "+f"(d[22]), "+f"(d[23]), "+f"(d[24]), "+f"(d[25]), "+f"(d[26]), "+f"(d[27])
    : "l"(da), "l"(db), "r"(sc), "n"(TA), "n"(TB));
}
template<int TA, int TB> __device__ __forceinline__ void wgmma_n64(float* d, uint64_t da, uint64_t db, int sc) {
  asm volatile("{\n.reg .pred p;\nsetp.ne.b32 p, %34, 0;\n"
    "wgmma.mma_async.sync.aligned.m64n64k16.f32.bf16.bf16 {%0, %1, %2, %3, %4, %5, %6, %7, %8, %9, %10, %11, %12, %13, %14, %15, %16, %17, %18, %19, %20, %21, %22, %23, %24, %25, %26, %27, %28, %29, %30, %31}, %32, %33, p, 1, 1, %35, %36;\n}\n"
    : "+f"(d[0]), "+f"(d[1]), "+f"(d[2]), "+f"(d[3]), "+f"(d[4]), "+f"(d[5]), "+f"(d[6]), "+f"(d[7]), "+f"(d[8]), "+f"(d[9]), "+f"(d[10]), "+f"(d[11]), "+f"(d[12]), "+f"(d[13]), "+f"(d[14]), "+f"(d[15]), "+f"(d[16]), "+f"(d[17]), "+f"(d[18]), "+f"(d[19]), "+f"(d[20]), "+f"(d[21]), "+f"(d[22]), "+f"(d[23]), "+f"(d[24]), "+f"(d[25]), "+f"(d[26]), "+f"(d[27]), "+f"(d[28]), "+f"(d[29]), "+f"(d[30]), "+f"(d[31])
    : "l"(da), "l"(db), "r"(sc), "n"(TA), "n"(TB));
}
template<int TA, int TB> __device__ __forceinline__ void wgmma_n72(float* d, uint64_t da, uint64_t db, int sc) {
  asm volatile("{\n.reg .pred p;\nsetp.ne.b32 p, %38, 0;\n"
    "wgmma.mma_async.sync.aligned.m64n72k16.f32.bf16.bf16 {%0, %1, %2, %3, %4, %5, %6, %7, %8, %9, %10, %11, %12, %13, %14, %15, %16, %17, %18, %19, %20, %21, %22, %23, %24, %25, %26, %27, %28, %29, %30, %31, %32, %33, %34, %35}, %36, %37, p, 1, 1, %39, %40;\n}\n"
    : "+f"(d[0]), "+f"(d[1]), "+f"(d[2]), "+f"(d[3]), "+f"(d[4]), "+f"(d[5]), "+f"(d[6]), "+f"(d[7]), "+f"(d[8]), "+f"(d[9]), "+f"(d[10]), "+f"(d[11]), "+f"(d[12]), "+f"(d[13]), "+f"(d[14]), "+f"(d[15]), "+f"(d[16]), "+f"(d[17]), "+f"(d[18]), "+f"(d[19]), "+f"(d[20]), "+f"(d[21]), "+f"(d[22]), "+f"(d[23]), "+f"(d[24]), "+f"(d[25]), "+f"(d[26]), "+f"(d[27]), "+f"(d[28]), "+f"(d[29]), "+f"(d[30]), "+f"(d[31]), "+f"(d[32]), "+f"(d[33]), "+f"(d[34]), "+f"(d[35])
    : "l"(da), "l"(db), "r"(sc), "n"(TA), "n"(TB));
}
template<int TA, int TB> __device__ __forceinline__ void wgmma_n80(float* d, uint64_t da, uint64_t db, int sc) {
  asm volatile("{\n.reg .pred p;\nsetp.ne.b32 p, %42, 0;\n"
    "wgmma.mma_async.sync.aligned.m64n80k16.f32.bf16.bf16 {%0, %1, %2, %3, %4, %5, %6, %7, %8, %9, %10, %11, %12, %13, %14, %15, %16, %17, %18, %19, %20, %21, %22, %23, %24, %25, %26, %27, %28, %29, %30, %31, %32, %33, %34, %35, %36, %37, %38, %39}, %40, %41, p, 1, 1, %43, %44;\n}\n"
    : "+f"(d[0]), "+f"(d[1]), "+f"(d[2]), "+f"(d[3]), "+f"(d[4]), "+f"(d[5]), "+f"(d[6]), "+f"(d[7]), "+f"(d[8]), "+f"(d[9]), "+f"(d[10]), "+f"(d[11]), "+f"(d[12]), "+f"(d[13]), "+f"(d[14]), "+f"(d[15]), "+f"(d[16]), "+f"(d[17]), "+f"(d[18]), "+f"(d[19]), "+f"(d[20]), "+f"(d[21]), "+f"(d[22]), "+f"(d[23]), "+f"(d[24]), "+f"(d[25]), "+f"(d[26]), "+f"(d[27]), "+f"(d[28]), "+f"(d[29]), "+f"(d[30]), "+f"(d[31]), "+f"(d[32]), "+f"(d[33]), "+f"(d[34]), "+f"(d[35]), "+f"(d[36]), "+f"(d[37]), "+f"(d[38]), "+f"(d[39])
    : "l"(da), "l"(db), "r"(sc), "n"(TA), "n"(TB));
}
template<int TA, int TB> __device__ __forceinline__ void wgmma_n88(float* d, uint64_t da, uint64_t db, int sc) {
  asm volatile("{\n.reg .pred p;\nsetp.ne.b32 p, %46, 0;\n"
    "wgmma.mma_async.sync.aligned.m64n88k16.f32.bf16.bf16 {%0, %1, %2, %3, %4, %5, %6, %7, %8, %9, %10, %11, %12, %13, %14, %15, %16, %17, %18, %19, %20, %21, %22, %23, %24, %25, %26, %27, %28, %29, %30, %31, %32, %33, %34, %35, %36, %37, %38, %39, %40, %41, %42, %43}, %44, %45, p, 1, 1, %47, %48;\n}\n"
    : "+f"(d[0]), "+f"(d[1]), "+f"(d[2]), "+f"(d[3]), "+f"(d[4]), "+f"(d[5]), "+f"(d[6]), "+f"(d[7]), "+f"(d[8]), "+f"(d[9]), "+f"(d[10]), "+f"(d[11]), "+f"(d[12]), "+f"(d[13]), "+f"(d[14]), "+f"(d[15]), "+f"(d[16]), "+f"(d[17]), "+f"(d[18]), "+f"(d[19]), "+f"(d[20]), "+f"(d[21]), "+f"(d[22]), "+f"(d[23]), "+f"(d[24]), "+f"(d[25]), "+f"(d[26]), "+f"(d[27]), "+f"(d[28]), "+f"(d[29]), "+f"(d[30]), "+f"(d[31]), "+f"(d[32]), "+f"(d[33]), "+f"(d[34]), "+f"(d[35]), "+f"(d[36]), "+f"(d[37]), "+f"(d[38]), "+f"(d[39]), "+f"(d[40]), "+f"(d[41]), "+f"(d[42]), "+f"(d[43])
    : "l"(da), "l"(db), "r"(sc), "n"(TA), "n"(TB));
}
template<int TA, int TB> __device__ __forceinline__ void wgmma_n96(float* d, uint64_t da, uint64_t db, int sc) {
  asm volatile("{\n.reg .pred p;\nsetp.ne.b32 p, %50, 0;\n"
    "wgmma.mma_async.sync.aligned.m64n96k16.f32.bf16.bf16 {%0, %1, %2, %3, %4, %5, %6, %7, %8, %9, %10, %11, %12, %13, %14, %15, %16, %17, %18, %19, %20, %21, %22, %23, %24, %25, %26, %27, %28, %29, %30, %31, %32, %33, %34, %35, %36, %37, %38, %39, %40, %41, %42, %43, %44, %45, %46, %47}, %48, %49, p, 1, 1, %51, %52;\n}\n"
    : "+f"(d[0]), "+f"(d[1]), "+f"(d[2]), "+f"(d[3]), "+f"(d[4]), "+f"(d[5]), "+f"(d[6]), "+f"(d[7]), "+f"(d[8]), "+f"(d[9]), "+f"(d[10]), "+f"(d[11]), "+f"(d[12]), "+f"(d[13]), "+f"(d[14]), "+f"(d[15]), "+f"(d[16]), "+f"(d[17]), "+f"(d[18]), "+f"(d[19]), "+f"(d[20]), "+f"(d[21]), "+f"(d[22]), "+f"(d[23]), "+f"(d[24]), "+f"(d[25]), "+f"(d[26]), "+f"(d[27]), "+f"(d[28]), "+f"(d[29]), "+f"(d[30]), "+f"(d[31]), "+f"(d[32]), "+f"(d[33]), "+f"(d[34]), "+f"(d[35]), "+f"(d[36]), "+f"(d[37]), "+f"(d[38]), "+f"(d[39]), "+f"(d[40]), "+f"(d[41]), "+f"(d[42]), "+f"(d[43]), "+f"(d[44]), "+f"(d[45]), "+f"(d[46]), "+f"(d[47])
    : "l"(da), "l"(db), "r"(sc), "n"(TA), "n"(TB));
}
template<int TA, int TB> __device__ __forceinline__ void wgmma_n104(float* d, uint64_t da, uint64_t db, int sc) {
  asm volatile("{\n.reg .pred p;\nsetp.ne.b32 p, %54, 0;\n"
    "wgmma.mma_async.sync.aligned.m64n104k16.f32.bf16.bf16 {%0, %1, %2, %3, %4, %5, %6, %7, %8, %9, %10, %11, %12, %13, %14, %15, %16, %17, %18, %19, %20, %21, %22, %23, %24, %25, %26, %27, %28, %29, %30, %31, %32, %33, %34, %35, %36, %37, %38, %39, %40, %41, %42, %43, %44, %45, %46, %47, %48, %49, %50, %51}, %52, %53, p, 1, 1, %55, %56;\n}\n"
    : "+f"(d[0]), "+f"(d[1]), "+f"(d[2]), "+f"(d[3]), "+f"(d[4]), "+f"(d[5]), "+f"(d[6]), "+f"(d[7]), "+f"(d[8]), "+f"(d[9]), "+f"(d[10]), "+f"(d[11]), "+f"(d[12]), "+f"(d[13]), "+f"(d[14]), "+f"(d[15]), "+f"(d[16]), "+f"(d[17]), "+f"(d[18]), "+f"(d[19]), "+f"(d[20]), "+f"(d[21]), "+f"(d[22]), "+f"(d[23]), "+f"(d[24]), "+f"(d[25]), "+f"(d[26]), "+f"(d[27]), "+f"(d[28]), "+f"(d[29]), "+f"(d[30]), "+f"(d[31]), "+f"(d[32]), "+f"(d[33]), "+f"(d[34]), "+f"(d[35]), "+f"(d[36]), "+f"(d[37]), "+f"(d[38]), "+f"(d[39]), "+f"(d[40]), "+f"(d[41]), "+f"(d[42]), "+f"(d[43]), "+f"(d[44]), "+f"(d[45]), "+f"(d[46]), "+f"(d[47]), "+f"(d[48]), "+f"(d[49]), "+f"(d[50]), "+f"(d[51])
    : "l"(da), "l"(db), "r"(sc), "n"(TA), "n"(TB));
}
template<int TA, int TB> __device__ __forceinline__ void wgmma_n112(float* d, uint64_t da, uint64_t db, int sc) {
  asm volatile("{\n.reg .pred p;\nsetp.ne.b32 p, %58, 0;\n"
    "wgmma.mma_async.sync.aligned.m64n112k16.f32.bf16.bf16 {%0, %1, %2, %3, %4, %5, %6, %7, %8, %9, %10, %11, %12, %13, %14, %15, %16, %17, %18, %19, %20, %21, %22, %23, %24, %25, %26, %27, %28, %29, %30, %31, %32, %33, %34, %35, %36, %37, %38, %39, %40, %41, %42, %43, %44, %45, %46, %47, %48, %49, %50, %51, %52, %53, %54, %55}, %56, %57, p, 1, 1, %59, %60;\n}\n"
    : "+f"(d[0]), "+f"(d[1]), "+f"(d[2]), "+f"(d[3]), "+f"(d[4]), "+f"(d[5]), "+f"(d[6]), "+f"(d[7]), "+f"(d[8]), "+f"(d[9]), "+f"(d[10]), "+f"(d[11]), "+f"(d[12]), "+f"(d[13]), "+f"(d[14]), "+f"(d[15]), "+f"(d[16]), "+f"(d[17]), "+f"(d[18]), "+f"(d[19]), "+f"(d[20]), "+f"(d[21]), "+f"(d[22]), "+f"(d[23]), "+f"(d[24]), "+f"(d[25]), "+f"(d[26]), "+f"(d[27]), "+f"(d[28]), "+f"(d[29]), "+f"(d[30]), "+f"(d[31]), "+f"(d[32]), "+f"(d[33]), "+f"(d[34]), "+f"(d[35]), "+f"(d[36]), "+f"(d[37]), "+f"(d[38]), "+f"(d[39]), "+f"(d[40]), "+f"(d[41]), "+f"(d[42]), "+f"(d[43]), "+f"(d[44]), "+f"(d[45]), "+f"(d[46]), "+f"(d[47]), "+f"(d[48]), "+f"(d[49]), "+f"(d[50]), "+f"(d[51]), "+f"(d[52]), "+f"(d[53]), "+f"(d[54]), "+f"(d[55])
    : "l"(da), "l"(db), "r"(sc), "n"(TA), "n"(TB));
}
template<int TA, int TB> __device__ __forceinline__ void wgmma_n120(float* d, uint64_t da, uint64_t db, int sc) {
  asm volatile("{\n.reg .pred p;\nsetp.ne.b32 p, %62, 0;\n"
    "wgmma.mma_async.sync.aligned.m64n120k16.f32.bf16.bf16 {%0, %1, %2, %3, %4, %5, %6, %7, %8, %9, %10, %11, %12, %13, %14, %15, %16, %17, %18, %19, %20, %21, %22, %23, %24, %25, %26, %27, %28, %29, %30, %31, %32, %33, %34, %35, %36, %37, %38, %39, %40, %41, %42, %43, %44, %45, %46, %47, %48, %49, %50, %51, %52, %53, %54, %55, %56, %57, %58, %59}, %60, %61, p, 1, 1, %63, %64;\n}\n"
    : "+f"(d[0]), "+f"(d[1]), "+f"(d[2]), "+f"(d[3]), "+f"(d[4]), "+f"(d[5]), "+f"(d[6]), "+f"(d[7]), "+f"(d[8]), "+f"(d[9]), "+f"(d[10]), "+f"(d[11]), "+f"(d[12]), "+f"(d[13]), "+f"(d[14]), "+f"(d[15]), "+f"(d[16]), "+f"(d[17]), "+f"(d[18]), "+f"(d[19]), "+f"(d[20]), "+f"(d[21]), "+f"(d[22]), "+f"(d[23]), "+f"(d[24]), "+f"(d[25]), "+f"(d[26]), "+f"(d[27]), "+f"(d[28]), "+f"(d[29]), "+f"(d[30]), "+f"(d[31]), "+f"(d[32]), "+f"(d[33]), "+f"(d[34]), "+f"(d[35]), "+f"(d[36]), "+f"(d[37]), "+f"(d[38]), "+f"(d[39]), "+f"(d[40]), "+f"(d[41]), "+f"(d[42]), "+f"(d[43]), "+f"(d[44]), "+f"(d[45]), "+f"(d[46]), "+f"(d[47]), "+f"(d[48]), "+f"(d[49]), "+f"(d[50]), "+f"(d[51]), "+f"(d[52]), "+f"(d[53]), "+f"(d[54]), "+f"(d[55]), "+f"(d[56]), "+f"(d[57]), "+f"(d[58]), "+f"(d[59])
    : "l"(da), "l"(db), "r"(sc), "n"(TA), "n"(TB));
}
template<int TA, int TB> __device__ __forceinline__ void wgmma_n128(float* d, uint64_t da, uint64_t db, int sc) {
  asm volatile("{\n.reg .pred p;\nsetp.ne.b32 p, %66, 0;\n"
    "wgmma.mma_async.sync.aligned.m64n128k16.f32.bf16.bf16 {%0, %1, %2, %3, %4, %5, %6, %7, %8, %9, %10, %11, %12, %13, %14, %15, %16, %17, %18, %19, %20, %21, %22, %23, %24, %25, %26, %27, %28, %29, %30, %31, %32, %33, %34, %35, %36, %37, %38, %39, %40, %41, %42, %43, %44, %45, %46, %47, %48, %49, %50, %51, %52, %53, %54, %55, %56, %57, %58, %59, %60, %61, %62, %63}, %64, %65, p, 1, 1, %67, %68;\n}\n"
    : "+f"(d[0]), "+f"(d[1]), "+f"(d[2]), "+f"(d[3]), "+f"(d[4]), "+f"(d[5]), "+f"(d[6]), "+f"(d[7]), "+f"(d[8]), "+f"(d[9]), "+f"(d[10]), "+f"(d[11]), "+f"(d[12]), "+f"(d[13]), "+f"(d[14]), "+f"(d[15]), "+f"(d[16]), "+f"(d[17]), "+f"(d[18]), "+f"(d[19]), "+f"(d[20]), "+f"(d[21]), "+f"(d[22]), "+f"(d[23]), "+f"(d[24]), "+f"(d[25]), "+f"(d[26]), "+f"(d[27]), "+f"(d[28]), "+f"(d[29]), "+f"(d[30]), "+f"(d[31]), "+f"(d[32]), "+f"(d[33]), "+f"(d[34]), "+f"(d[35]), "+f"(d[36]), "+f"(d[37]), "+f"(d[38]), "+f"(d[39]), "+f"(d[40]), "+f"(d[41]), "+f"(d[42]), "+f"(d[43]), "+f"(d[44]), "+f"(d[45]), "+f"(d[46]), "+f"(d[47]), "+f"(d[48]), "+f"(d[49]), "+f"(d[50]), "+f"(d[51]), "+f"(d[52]), "+f"(d[53]), "+f"(d[54]), "+f"(d[55]), "+f"(d[56]), "+f"(d[57]), "+f"(d[58]), "+f"(d[59]), "+f"(d[60]), "+f"(d[61]), "+f"(d[62]), "+f"(d[63])
    : "l"(da), "l"(db), "r"(sc), "n"(TA), "n"(TB));
}
template<int TA, int TB> __device__ __forceinline__ void wgmma_n160(float* d, uint64_t da, uint64_t db, int sc) {
  asm volatile("{\n.reg .pred p;\nsetp.ne.b32 p, %82, 0;\n"
    "wgmma.mma_async.sync.aligned.m64n160k16.f32.bf16.bf16 {%0, %1, %2, %3, %4, %5, %6, %7, %8, %9, %10, %11, %12, %13, %14, %15, %16, %17, %18, %19, %20, %21, %22, %23, %24, %25, %26, %27, %28, %29, %30, %31, %32, %33, %34, %35, %36, %37, %38, %39, %40, %41, %42, %43, %44, %45, %46, %47, %48, %49, %50, %51, %52, %53, %54, %55, %56, %57, %58, %59, %60, %61, %62, %63, %64, %65, %66, %67, %68, %69, %70, %71, %72, %73, %74, %75, %76, %77, %78, %79}, %80, %81, p, 1, 1, %83, %84;\n}\n"
    : "+f"(d[0]), "+f"(d[1]), "+f"(d[2]), "+f"(d[3]), "+f"(d[4]), "+f"(d[5]), "+f"(d[6]), "+f"(d[7]), "+f"(d[8]), "+f"(d[9]), "+f"(d[10]), "+f"(d[11]), "+f"(d[12]), "+f"(d[13]), "+f"(d[14]), "+f"(d[15]), "+f"(d[16]), "+f"(d[17]), "+f"(d[18]), "+f"(d[19]), "+f"(d[20]), "+f"(d[21]), "+f"(d[22]), "+f"(d[23]), "+f"(d[24]), "+f"(d[25]), "+f"(d[26]), "+f"(d[27]), "+f"(d[28]), "+f"(d[29]), "+f"(d[30]), "+f"(d[31]), "+f"(d[32]), "+f"(d[33]), "+f"(d[34]), "+f"(d[35]), "+f"(d[36]), "+f"(d[37]), "+f"(d[38]), "+f"(d[39]), "+f"(d[40]), "+f"(d[41]), "+f"(d[42]), "+f"(d[43]), "+f"(d[44]), "+f"(d[45]), "+f"(d[46]), "+f"(d[47]), "+f"(d[48]), "+f"(d[49]), "+f"(d[50]), "+f"(d[51]), "+f"(d[52]), "+f"(d[53]), "+f"(d[54]), "+f"(d[55]), "+f"(d[56]), "+f"(d[57]), "+f"(d[58]), "+f"(d[59]), "+f"(d[60]), "+f"(d[61]), "+f"(d[62]), "+f"(d[63]), "+f"(d[64]), "+f"(d[65]), "+f"(d[66]), "+f"(d[67]), "+f"(d[68]), "+f"(d[69]), "+f"(d[70]), "+f"(d[71]), "+f"(d[72]), "+f"(d[73]), "+f"(d[74]), "+f"(d[75]), "+f"(d[76]), "+f"(d[77]), "+f"(d[78]), "+f"(d[79])
    : "l"(da), "l"(db), "r"(sc), "n"(TA), "n"(TB));
}
template<int TA, int TB> __device__ __forceinline__ void wgmma_n192(float* d, uint64_t da, uint64_t db, int sc) {
  asm volatile("{\n.reg .pred p;\nsetp.ne.b32 p, %98, 0;\n"
    "wgmma.mma_async.sync.aligned.m64n192k16.f32.bf16.bf16 {%0, %1, %2, %3, %4, %5, %6, %7, %8, %9, %10, %11, %12, %13, %14, %15, %16, %17, %18, %19, %20, %21, %22, %23, %24, %25, %26, %27, %28, %29, %30, %31, %32, %33, %34, %35, %36, %37, %38, %39, %40, %41, %42, %43, %44, %45, %46, %47, %48, %49, %50, %51, %52, %53, %54, %55, %56, %57, %58, %59, %60, %61, %62, %63, %64, %65, %66, %67, %68, %69, %70, %71, %72, %73, %74, %75, %76, %77, %78, %79, %80, %81, %82, %83, %84, %85, %86, %87, %88, %89, %90, %91, %92, %93, %94, %95}, %96, %97, p, 1, 1, %99, %100;\n}\n"
    : "+f"(d[0]), "+f"(d[1]), "+f"(d[2]), "+f"(d[3]), "+f"(d[4]), "+f"(d[5]), "+f"(d[6]), "+f"(d[7]), "+f"(d[8]), "+f"(d[9]), "+f"(d[10]), "+f"(d[11]), "+f"(d[12]), "+f"(d[13]), "+f"(d[14]), "+f"(d[15]), "+f"(d[16]), "+f"(d[17]), "+f"(d[18]), "+f"(d[19]), "+f"(d[20]), "+f"(d[21]), "+f"(d[22]), "+f"(d[23]), "+f"(d[24]), "+f"(d[25]), "+f"(d[26]), "+f"(d[27]), "+f"(d[28]), "+f"(d[29]), "+f"(d[30]), "+f"(d[31]), "+f"(d[32]), "+f"(d[33]), "+f"(d[34]), "+f"(d[35]), "+f"(d[36]), "+f"(d[37]), "+f"(d[38]), "+f"(d[39]), "+f"(d[40]), "+f"(d[41]), "+f"(d[42]), "+f"(d[43]), "+f"(d[44]), "+f"(d[45]), "+f"(d[46]), "+f"(d[47]), "+f"(d[48]), "+f"(d[49]), "+f"(d[50]), "+f"(d[51]), "+f"(d[52]), "+f"(d[53]), "+f"(d[54]), "+f"(d[55]), "+f"(d[56]), "+f"(d[57]), "+f"(d[58]), "+f"(d[59]), "+f"(d[60]), "+f"(d[61]), "+f"(d[62]), "+f"(d[63]), "+f"(d[64]), "+f"(d[65]), "+f"(d[66]), "+f"(d[67]), "+f"(d[68]), "+f"(d[69]), "+f"(d[70]), "+f"(d[71]), "+f"(d[72]), "+f"(d[73]), "+f"(d[74]), "+f"(d[75]), "+f"(d[76]), "+f"(d[77]), "+f"(d[78]), "+f"(d[79]), "+f"(d[80]), "+f"(d[81]), "+f"(d[82]), "+f"(d[83]), "+f"(d[84]), "+f"(d[85]), "+f"(d[86]), "+f"(d[87]), "+f"(d[88]), "+f"(d[89]), "+f"(d[90]), "+f"(d[91]), "+f"(d[92]), "+f"(d[93]), "+f"(d[94]), "+f"(d[95])
    : "l"(da), "l"(db), "r"(sc), "n"(TA), "n"(TB));
}
template<int N, int TA, int TB> __device__ __forceinline__ void wgmma_ss(float* d, uint64_t da, uint64_t db, int sc) {
  if constexpr (N == 8) wgmma_n8<TA,TB>(d, da, db, sc);
  if constexpr (N == 16) wgmma_n16<TA,TB>(d, da, db, sc);
  if constexpr (N == 24) wgmma_n24<TA,TB>(d, da, db, sc);
  if constexpr (N == 32) wgmma_n32<TA,TB>(d, da, db, sc);
  if constexpr (N == 40) wgmma_n40<TA,TB>(d, da, db, sc);
  if constexpr (N == 48) wgmma_n48<TA,TB>(d, da, db, sc);
  if constexpr (N == 56) wgmma_n56<TA,TB>(d, da, db, sc);
  if constexpr (N == 64) wgmma_n64<TA,TB>(d, da, db, sc);
  if constexpr (N == 72) wgmma_n72<TA,TB>(d, da, db, sc);
  if constexpr (N == 80) wgmma_n80<TA,TB>(d, da, db, sc);
  if constexpr (N == 88) wgmma_n88<TA,TB>(d, da, db, sc);
  if constexpr (N == 96) wgmma_n96<TA,TB>(d, da, db, sc);
  if constexpr (N == 104) wgmma_n104<TA,TB>(d, da, db, sc);
  if constexpr (N == 112) wgmma_n112<TA,TB>(d, da, db, sc);
  if constexpr (N == 120) wgmma_n120<TA,TB>(d, da, db, sc);
  if constexpr (N == 128) wgmma_n128<TA,TB>(d, da, db, sc);
  if constexpr (N == 160) wgmma_n160<TA,TB>(d, da, db, sc);
  if constexpr (N == 192) wgmma_n192<TA,TB>(d, da, db, sc);
}

constexpr int NGRP = 260;
constexpr uint32_t G1_STAGE = 57344;
constexpr uint32_t OFF_U = 131072;
constexpr uint32_t OFF_H = 172032;
constexpr uint32_t H_PITCH = 4352;
constexpr uint32_t OFF_ZS = 215552;
constexpr uint32_t OFF_EX = OFF_ZS + 12544;
constexpr uint32_t OFF_G = OFF_EX + 2304;
constexpr uint32_t OFF_BAR = OFF_G + 640;
constexpr uint32_t OFF_GS = OFF_BAR + 384;
constexpr uint32_t SMEM_BYTES = OFF_GS + 64 + 512;
constexpr uint32_t OFF_V = OFF_H + 23040;
constexpr uint32_t OFF_US = OFF_ZS + 1536;
constexpr int NCTA = 130;
constexpr uint32_t SB0 = 1024;

enum { B_FULL1 = 0, B_KV = 3,
       B_FULL2 = 4, B_EMPTY2 = 8, B_CD = 12, B_HLD = 17, B_QG = 18, B_GATE = 19, B_GS = 20,
       B_HDR = 21, B_XF = 22, B_XCH = 23, B_Z = 25,
       B_EMPTY1 = 26, B_G1DONE = 29,
       B_R2FREE = 30, B_UFULL = 31,
       B_SIGH = 36, B_SIGZ = 40, B_COUNT = 45 };
enum { C_H = 0, C_U = 16, C_Z = 24, C_DONE = 34, C_COUNT = 35 };
__host__ __device__ constexpr uint32_t slotF(int s) { return s == 0 ? 114688 : s == 1 ? 32768 : s == 2 ? 90112 : 49152; }
__host__ __device__ constexpr uint32_t slotO(int s) { return s == 3 ? 106496 : slotF(s) + 8192; }
__host__ __device__ constexpr uint32_t slotB0(int s) { return s == 0 ? 0 : s == 1 ? 20480 : s == 2 ? 67584 : 155648; }
__host__ __device__ constexpr uint32_t slotB1(int s) { return s == 1 ? 57344 : slotB0(s) + 10240; }
constexpr uint32_t OFF_Q = 176128, OFF_Z = 131072, OFF_XCH = 196608;
__device__ __forceinline__ uint32_t zstage(int ch) { return ch < 3 ? OFF_ZS + ch * 4160 : ch == 3 ? 198656 : 208896; }

__device__ __align__(1024) __nv_bfloat16 g_Hs[48 * NGRP * 256];
__device__ __align__(1024) __nv_bfloat16 g_U[640 * 2 * 2048];
__device__ __align__(1024) __nv_bfloat16 g_zT[640 * NGRP * 8];
__device__ __align__(1024) float g_gate[NGRP * 8];
__device__ __align__(1024) unsigned g_cnt[C_COUNT * 32];
#define TS(i) do { } while (0)
#define TSB(i) do { } while (0)

__device__ __forceinline__ uint32_t smem_u32(const void* p) { return (uint32_t)__cvta_generic_to_shared(p); }
__device__ __forceinline__ int fresh_lane() {
  int r;
  asm volatile("mov.u32 %0, %%laneid;" : "=r"(r));
  return r;
}
__device__ __forceinline__ uint64_t mkdesc(uint32_t addr, uint32_t lbo, uint32_t sbo, uint32_t swz) {
  return (uint64_t)((addr & 0x3FFFF) >> 4) | ((uint64_t)(lbo >> 4) << 16) | ((uint64_t)(sbo >> 4) << 32) | ((uint64_t)swz << 62);
}
__device__ __forceinline__ void wg_fence() { asm volatile("wgmma.fence.sync.aligned;" ::: "memory"); }
__device__ __forceinline__ void wg_commit() { asm volatile("wgmma.commit_group.sync.aligned;" ::: "memory"); }
template <int N> __device__ __forceinline__ void wg_wait() { asm volatile("wgmma.wait_group.sync.aligned %0;" ::"n"(N) : "memory"); }
template <int N> __device__ __forceinline__ void pin(float* d) {
#pragma unroll
  for (int i = 0; i < N; i++) asm volatile("" : "+f"(d[i])::"memory");
}
__device__ __forceinline__ void mbar_init(uint32_t a, int c) { asm volatile("mbarrier.init.shared::cta.b64 [%0], %1;" ::"r"(a), "r"(c) : "memory"); }
__device__ __forceinline__ void mbar_expect(uint32_t a, uint32_t b) { asm volatile("mbarrier.arrive.expect_tx.shared::cta.b64 _, [%0], %1;" ::"r"(a), "r"(b) : "memory"); }
__device__ __forceinline__ uint32_t peer_addr(uint32_t a) {
  uint32_t r;
  asm("mapa.shared::cluster.u32 %0, %1, %2;" : "=r"(r) : "r"(a), "r"((blockIdx.x & 1) ^ 1));
  return r;
}
__device__ __forceinline__ void mbar_arrive(uint32_t a) { asm volatile("mbarrier.arrive.shared::cta.b64 _, [%0];" ::"r"(a) : "memory"); }
__device__ __forceinline__ bool elect_one() {
  uint32_t e;
  asm volatile("{\n.reg .pred p;\nelect.sync _|p, 0xffffffff;\nselp.u32 %0,1,0,p;\n}" : "=r"(e));
  return e;
}
__device__ __forceinline__ void mbar_wait_t(uint32_t a, uint32_t ph) {
  asm volatile(
      "{\n.reg .pred p, q;\n.reg .u32 n;\n"
      "mbarrier.try_wait.parity.shared::cta.b64 p, [%0], %1;\n"
      "@p bra DONE_%=;\n"
      "mov.u32 n, 0;\n"
      "WAIT_%=:\n"
      "mbarrier.try_wait.parity.shared::cta.b64 p, [%0], %1;\n"
      "@p bra DONE_%=;\n"
      "add.u32 n, n, 1;\n"
      "setp.lt.u32 q, n, 0x40000;\n"
      "@q bra WAIT_%=;\n"
      "trap;\n"
      "DONE_%=:\n}" ::"r"(a), "r"(ph) : "memory");
}
__device__ __forceinline__ void mbar_wait(uint32_t a, uint32_t ph) {
  asm volatile(
      "{\n.reg .pred p, q;\n.reg .u32 n;\nmov.u32 n, 0;\n"
      "WAIT_%=:\n"
      "mbarrier.try_wait.parity.shared::cta.b64 p, [%0], %1;\n"
      "@p bra DONE_%=;\n"
      "add.u32 n, n, 1;\n"
      "setp.lt.u32 q, n, 0x80000;\n"
      "@q bra WAIT_%=;\n"
      "DONE_%=:\n}" ::"r"(a), "r"(ph) : "memory");
}
__device__ __forceinline__ void flag_wait(const unsigned* p0, const unsigned* p1, unsigned target) {
  int it = 0;
  while (true) {
    unsigned v0, v1;
    asm volatile("ld.relaxed.gpu.global.u32 %0, [%1];" : "=r"(v0) : "l"(p0) : "memory");
    asm volatile("ld.relaxed.gpu.global.u32 %0, [%1];" : "=r"(v1) : "l"(p1) : "memory");
    if (min(v0, v1) >= target) break;
    if (++it > (1 << 21)) __trap();
  }
  asm volatile("fence.proxy.async.global;" ::: "memory");
}
__device__ __forceinline__ void flag_add(unsigned* p) {
  asm volatile("red.relaxed.gpu.global.add.u32 [%0], 1;" ::"l"(p) : "memory");
}
__device__ __forceinline__ void bar_sync(int id, int n) { asm volatile("bar.sync %0, %1;" ::"r"(id), "r"(n) : "memory"); }
__device__ __forceinline__ void bar_arrive(int id, int n) { asm volatile("bar.arrive %0, %1;" ::"r"(id), "r"(n) : "memory"); }
__device__ __forceinline__ void bulk_g2s(uint32_t dst, const void* src, uint32_t bytes, uint32_t bar) {
  asm volatile("cp.async.bulk.shared::cluster.global.mbarrier::complete_tx::bytes [%0], [%1], %2, [%3];" ::"r"(dst), "l"(src), "r"(bytes), "r"(bar) : "memory");
}
__device__ __forceinline__ void bulk_s2g(void* dst, uint32_t src, uint32_t bytes) {
  asm volatile("cp.async.bulk.global.shared::cta.bulk_group [%0], [%1], %2;" ::"l"(dst), "r"(src), "r"(bytes) : "memory");
}
__device__ __forceinline__ void bulk_prefetch(const void* src, uint32_t bytes) {
  asm volatile("cp.async.bulk.prefetch.L2.global [%0], %1;" ::"l"(src), "r"(bytes) : "memory");
}
__device__ __forceinline__ void tma2(uint32_t dst, const CUtensorMap* m, int c0, int c1, uint32_t bar) {
  asm volatile("cp.async.bulk.tensor.2d.shared::cluster.global.mbarrier::complete_tx::bytes [%0], [%1, {%3,%4}], [%2];" ::"r"(dst), "l"(m), "r"(bar), "r"(c0), "r"(c1) : "memory");
}
__device__ __forceinline__ void tma3(uint32_t dst, const CUtensorMap* m, int c0, int c1, int c2, uint32_t bar) {
  asm volatile("cp.async.bulk.tensor.3d.shared::cluster.global.mbarrier::complete_tx::bytes [%0], [%1, {%3,%4,%5}], [%2];" ::"r"(dst), "l"(m), "r"(bar), "r"(c0), "r"(c1), "r"(c2) : "memory");
}
__device__ __forceinline__ void tma4(uint32_t dst, const CUtensorMap* m, int c0, int c1, int c2, int c3, uint32_t bar) {
  asm volatile("cp.async.bulk.tensor.4d.shared::cluster.global.mbarrier::complete_tx::bytes [%0], [%1, {%3,%4,%5,%6}], [%2];" ::"r"(dst), "l"(m), "r"(bar), "r"(c0), "r"(c1), "r"(c2), "r"(c3) : "memory");
}
__device__ __forceinline__ void prefetch_map(const CUtensorMap* m) { asm volatile("prefetch.tensormap [%0];" ::"l"(m) : "memory"); }
__device__ __forceinline__ void tma2_store(const CUtensorMap* m, uint32_t src, int c0, int c1) {
  asm volatile("cp.async.bulk.tensor.2d.global.shared::cta.bulk_group [%0, {%2,%3}], [%1];" ::"l"(m), "r"(src), "r"(c0), "r"(c1) : "memory");
}
__device__ __forceinline__ void tma3_store(const CUtensorMap* m, uint32_t src, int c0, int c1, int c2) {
  asm volatile("cp.async.bulk.tensor.3d.global.shared::cta.bulk_group [%0, {%2,%3,%4}], [%1];" ::"l"(m), "r"(src), "r"(c0), "r"(c1), "r"(c2) : "memory");
}
__device__ __forceinline__ void tma4_store(const CUtensorMap* m, uint32_t src, int c0, int c1, int c2, int c3) {
  asm volatile("cp.async.bulk.tensor.4d.global.shared::cta.bulk_group [%0, {%2,%3,%4,%5}], [%1];" ::"l"(m), "r"(src), "r"(c0), "r"(c1), "r"(c2), "r"(c3) : "memory");
}
__device__ __forceinline__ uint32_t pack_bf16(float lo, float hi) {
  uint32_t r;
  asm("cvt.rn.bf16x2.f32 %0, %1, %2;" : "=r"(r) : "f"(hi), "f"(lo));
  return r;
}
__device__ __forceinline__ float tanh_fast(float x) {
  float r;
  asm("tanh.approx.f32 %0, %1;" : "=f"(r) : "f"(x));
  return r;
}
__device__ __forceinline__ uint32_t bmul2(uint32_t a, uint32_t b) {
  uint32_t r;
  asm("mul.rn.bf16x2 %0, %1, %2;" : "=r"(r) : "r"(a), "r"(b));
  return r;
}
__device__ __forceinline__ uint32_t bfma2(uint32_t a, uint32_t b, uint32_t c) {
  uint32_t r;
  asm("fma.rn.bf16x2 %0, %1, %2, %3;" : "=r"(r) : "r"(a), "r"(b), "r"(c));
  return r;
}
__device__ __forceinline__ uint2 lds64(uint32_t a) {
  uint2 r;
  asm volatile("ld.volatile.shared.v2.u32 {%0,%1}, [%2];" : "=r"(r.x), "=r"(r.y) : "r"(a) : "memory");
  return r;
}
__device__ __forceinline__ float bflo(uint32_t v) { return __uint_as_float(v << 16); }
__device__ __forceinline__ float bfhi(uint32_t v) { return __uint_as_float(v & 0xffff0000u); }

__device__ __forceinline__ uint32_t badd2(uint32_t a, uint32_t b) {
  uint32_t r;
  asm("add.rn.bf16x2 %0, %1, %2;" : "=r"(r) : "r"(a), "r"(b));
  return r;
}
template <int I0, int I1> __device__ __forceinline__ void conv_mma(float* d, uint64_t da, uint64_t db) {
  if constexpr (I0 < I1) {
    constexpr int S = I0 >> 1, PH = I0 & 1;
    wgmma_ss<128 - 8 * S, 1, 1>(d, da + (PH * (H_PITCH >> 4) + 16 * S), db + (PH * 256 + 16 * S), I0 != 0);
    conv_mma<I0 + 1, I1>(d, da, db);
  }
}
__device__ __forceinline__ uint64_t conv_da(int ch) { return mkdesc(SB0 + OFF_H + ch * 2 * H_PITCH, 128, 32, 0); }
__device__ __forceinline__ uint64_t conv_db(int ch) { return mkdesc(SB0 + OFF_U + (4 - ch) * 8192, 128, 256, 0); }
__device__ __forceinline__ void sts128_if(bool p, uint32_t a, const uint32_t* v) {
  asm volatile("{\n.reg .pred p;\nsetp.ne.u32 p, %5, 0;\n@p st.shared.v4.u32 [%0], {%1,%2,%3,%4};\n}" ::"r"(a), "r"(v[0]), "r"(v[1]), "r"(v[2]), "r"(v[3]), "r"((uint32_t)p) : "memory");
}
__device__ __forceinline__ void lds128_if(bool p, uint32_t a, uint32_t* v) {
  asm volatile("{\n.reg .pred p;\nsetp.ne.u32 p, %5, 0;\n@p ld.shared.v4.u32 {%0,%1,%2,%3}, [%4];\n}" : "+r"(v[0]), "+r"(v[1]), "+r"(v[2]), "+r"(v[3]) : "r"(a), "r"((uint32_t)p) : "memory");
}
__host__ __device__ constexpr int cvs(int next, int i) {
  constexpr int a[8] = {0, 2, 4, 6, 8, 11, 13, 15}, b[8] = {CV4};
  return CV0 + (next == 1 ? a[i] : b[i]) > 32 ? 32 : CV0 + (next == 1 ? a[i] : b[i]);
}
template <int NEXT>
__device__ __forceinline__ void conv_finish(const float* d, uint32_t sb, uint32_t bar, int ch, int wg, int w, float* dn, uint64_t da, uint64_t db) {
  const int lane = fresh_lane();
  const int g = lane >> 2, q = lane & 3;
  const int c = q & 1, mu = 8 * (q >> 1) + g;
  const int mu1 = (mu + 15) & 15, mu2 = (mu + (c ? 2 : 14)) & 15;
  const int src1 = 4 * (mu1 & 7) + 2 * (mu1 >> 3) + c;
  const int src2 = 4 * (mu2 & 7) + 2 * (mu2 >> 3) + (c ^ 1);
  const bool last = mu == 15, pA = (c == 0) || (mu >= 14);
  const bool impX = lane < 2, impY = (c == 1) && (mu >= 14);
  const int oo = 32 * w + (c ? mu2 : 16 + mu);
  const uint32_t zs = sb + zstage(ch);
  const uint32_t ex = sb + OFF_EX + (ch & 3) * 128 + (impX ? lane : 2 + (mu & 1)) * 32;
  uint32_t p0[8], xr[8], s1[8], e[8];
#pragma unroll
  for (int k = 0; k < 8; k++) {
    const int i = 60 - 8 * k;
    const uint32_t p1 = pack_bf16(d[i + 1], d[i - 3]), p3 = pack_bf16(d[i + 3], d[i - 1]);
    s1[k] = badd2(pack_bf16(d[i + 2], d[i - 2]), __shfl_sync(0xffffffffu, last ? p1 : p3, src1));
    xr[k] = __shfl_sync(0xffffffffu, last ? p3 : p1, src1);
    p0[k] = pack_bf16(d[i], d[i - 4]);
    if (NEXT && k == 1) conv_mma<cvs(NEXT, 0), cvs(NEXT, 1)>(dn, da, db);
    if (NEXT && k == 3) conv_mma<cvs(NEXT, 1), cvs(NEXT, 2)>(dn, da, db);
    if (NEXT && k == 5) conv_mma<cvs(NEXT, 2), cvs(NEXT, 3)>(dn, da, db);
    if (NEXT && k == 7) conv_mma<cvs(NEXT, 3), cvs(NEXT, 4)>(dn, da, db);
  }
  const uint32_t sh = w == 3 ? 0x5432 : 0x7654;
#pragma unroll
  for (int k = 0; k < 8; k++) e[k] = impX ? xr[k] : s1[k];
#pragma unroll
  for (int k = 7; k >= 0; k--) e[k] = __byte_perm(k ? e[k - 1] : 0u, e[k], sh);
  sts128_if(impX || impY, ex + ((w + 1) & 3) * 512, e);
  sts128_if(impX || impY, ex + ((w + 1) & 3) * 512 + 16, e + 4);
  if (NEXT) conv_mma<cvs(NEXT, 4), cvs(NEXT, 5)>(dn, da, db);
  bar_sync(3 + wg, 128);
  if (w == 0 && lane == 0) mbar_arrive(bar + 8 * (B_CD + ch));
  lds128_if(impX, ex + w * 512, xr);
  lds128_if(impX, ex + w * 512 + 16, xr + 4);
  lds128_if(impY, ex + w * 512, s1);
  lds128_if(impY, ex + w * 512 + 16, s1 + 4);
  if (NEXT) conv_mma<cvs(NEXT, 5), cvs(NEXT, 6)>(dn, da, db);
#pragma unroll
  for (int k = 0; k < 8; k++) {
    const uint32_t s0 = badd2(p0[k], xr[k]);
    e[k] = badd2(pA ? s1[k] : s0, __shfl_sync(0xffffffffu, pA ? s0 : s1[k], src2));
    if (NEXT && k == 3) conv_mma<cvs(NEXT, 6), cvs(NEXT, 7)>(dn, da, db);
  }
  const uint32_t z0 = zs + oo * 4 + (oo / 20) * 240, z1 = zs + (oo + 130) * 4 + ((oo + 130) / 20) * 240;
#pragma unroll
  for (int k = 0; k < 8; k++) asm volatile("st.shared.u32 [%0], %1;" ::"r"((k < 4 ? z0 : z1) + (k & 3) * 80), "r"(e[k]) : "memory");
  asm volatile("fence.proxy.async.shared::cta;" ::: "memory");
  __syncwarp();
  if (lane == 0) mbar_arrive(bar + 8 * (B_SIGZ + ch));
  if (NEXT) { conv_mma<cvs(NEXT, 7), 32>(dn, da, db); wg_commit(); }
}
template <int S, int OWN, int K0 = 0, int K1 = 4> __device__ __forceinline__ void g2_half(float* acc, uint64_t dA, uint64_t dB, int sc) {
#pragma unroll
  for (int kk = K0; kk < K1; kk++)
    wgmma_ss<160, 1, 0>(acc, dA + (((OWN ? slotO(S) : slotF(S)) >> 4) + 128 * kk), dB + (((kk < 2 ? slotB0(S) : slotB1(S)) >> 4) + 2 * (kk & 1)), kk ? 1 : sc);
}

template <int PART> __device__ __forceinline__ void glu_part(const float* acc, uint32_t dst) {
  constexpr int h = PART & 1, aa = PART >> 1;
  uint32_t v[4];
#pragma unroll
  for (int jj = 0; jj < 4; jj++) {
    const int i = 4 * (4 * aa + jj) + 2 * h;
    float t0 = tanh_fast(0.5f * acc[i]), t1 = tanh_fast(0.5f * acc[i + 1]);
    v[jj] = pack_bf16(fmaf(acc[48 + i], t0, acc[48 + i]), fmaf(acc[49 + i], t1, acc[49 + i]));
  }
  asm volatile("stmatrix.sync.aligned.m8n8.x4.shared.b16 [%0], {%1,%2,%3,%4};" ::"r"(dst + h * 1536 + aa * 512), "r"(v[0]), "r"(v[1]), "r"(v[2]), "r"(v[3]) : "memory");
}

struct Params {
  const __nv_bfloat16 *q, *k, *v, *w_gate, *w_up, *w_down, *shift_k, *ssm_k, *ssm_D, *gate_w;
  unsigned char perm[72];
};

__global__ void __cluster_dims__(2, 1, 1) __launch_bounds__(384, 1)
fused_kernel(const __grid_constant__ CUtensorMap mX, const __grid_constant__ CUtensorMap mWg,
             const __grid_constant__ CUtensorMap mWu, const __grid_constant__ CUtensorMap mWd,
             const __grid_constant__ CUtensorMap mQ, const __grid_constant__ CUtensorMap mZ,
             const __grid_constant__ CUtensorMap mO, const __grid_constant__ CUtensorMap mK,
             const __grid_constant__ CUtensorMap mV, const __grid_constant__ CUtensorMap mU,
             const __grid_constant__ CUtensorMap mH, const Params P) {
  extern __shared__ __align__(1024) unsigned char sm[];
  const uint32_t sb = smem_u32(sm);
  const uint32_t bar = sb + OFF_BAR;
  const int tid = threadIdx.x, warp = __shfl_sync(0xffffffffu, tid >> 5, 0), lane = tid & 31;
  if ((warp & 4) && elect_one()) prefetch_map(warp == 4 ? &mX : warp == 5 ? &mWg : warp == 6 ? &mWu : &mK);
  const int p2 = P.perm[blockIdx.x >> 1];
  const int cta = (p2 & 64) * 2 + (((p2 >> 1) & 4) | (p2 & 3)) * 16 + (((p2 >> 3) & 6) | ((p2 >> 2) & 1)) * 2 + (blockIdx.x & 1);
  const bool has1 = cta < 128;
  const int mb = cta >> 4, ft = cta & 15;
  const int rank = cta & 1;
  const int db = 2 * (p2 % 5) + rank;
  const int tb = p2 / 5;

  if (warp == 8) {
    if (has1 && elect_one()) {
#pragma unroll
      for (int kb = 0; kb < 3; kb++) {
        const int rg = (kb + 1) % 3;
        const uint32_t dst = sb + rg * G1_STAGE, fb = bar + 8 * (B_FULL1 + rg);
        mbar_init(fb, 1);
        mbar_expect(fb, G1_STAGE + (kb == 0 ? 1280 : 0));
        asm volatile("fence.proxy.async.shared::cta;" ::: "memory");
        tma4(dst, &mX, kb * 64, 0, (mb & 3) * 32, mb >> 2, fb);
        tma3(dst + 32768, &mWg, 0, kb * 64, ft * 3, fb);
        tma3(dst + 32768 + 12288, &mWu, 0, kb * 64, ft * 3, fb);
        if (kb == 0) bulk_g2s(sb + OFF_EX + 640, P.gate_w, 1280, fb);
      }
      mbar_init(bar + 8 * B_KV, 1);
      mbar_expect(bar + 8 * B_KV, 23040 + 21760 + 640);
      asm volatile("fence.proxy.async.shared::cta;" ::: "memory");
    }
  } else if (lane == 0) {
#pragma unroll
    for (int j = 0; j < 4; j++) {
      const int i = B_FULL2 + (warp > 8 ? warp - 1 : warp) + 11 * j;
      if (i < B_COUNT) mbar_init(bar + 8 * i, i < B_EMPTY1 ? 1 : i < B_R2FREE ? 2 : i < B_SIGH ? 3 : 4);
      if (i == B_XCH || i == B_XCH + 1) mbar_expect(bar + 8 * i, 10240);
    }
    asm volatile("fence.proxy.async.shared::cta;" ::: "memory");
  }
  __syncthreads();
  if (warp != 11) asm volatile("barrier.cluster.arrive.relaxed.aligned;" ::: "memory");

  if (warp < 8) {
    asm volatile("setmaxnreg.inc.sync.aligned.u32 224;");
    const int wg = warp >> 2, w = warp & 3;
    const bool elect = (tid & 127) == 0;
    if (has1) {
      const int lane = fresh_lane();
      float acc0[96], acc1[96];
      float *const d0 = acc0, *const d1 = acc1;
      {
        const uint64_t dA = mkdesc(G1SB + wg * 16384, 16, 1024, 1);
        const uint64_t dB = mkdesc(G1SB + 32768, 4096, 512, 2);
#pragma unroll 1
        for (int kb = 0; kb < 8; kb++) {
          const int rg = (kb + 1) % 3;
          const uint64_t da = dA + rg * (G1_STAGE >> 4), db = dB + rg * (G1_STAGE >> 4);
          if (tid == 0 && kb >= 6) TSB(70 + kb);
          mbar_wait(bar + 8 * (B_FULL1 + rg), (kb / 3) & 1);
          if (tid == 0) TS(kb == 0 ? 1 : 46 + kb);
          wg_fence();
#pragma unroll
          for (int kk = 0; kk < REL; kk++) wgmma_ss<192, 0, 1>(acc0, da + 2 * kk, db + 64 * kk, (kb | kk) != 0);
          wg_commit();
          wg_wait<1>();
          if (kb > 0 && elect) mbar_arrive(bar + 8 * (B_EMPTY1 + kb % 3));
          wg_fence();
#pragma unroll
          for (int kk = REL; kk < 4; kk++) wgmma_ss<192, 0, 1>(acc0, da + 2 * kk, db + 64 * kk, 1);
#pragma unroll
          for (int kk = 0; kk < 4; kk++) wgmma_ss<192, 0, 1>(acc1, da + 512 + 2 * kk, db + 64 * kk, (kb | kk) != 0);
          wg_commit();
        }
#define G1_MMA(ACC, J) wgmma_ss<192, 0, 1>(ACC == 0 ? acc0 : acc1, dA + (((J) >> 2) * (G1_STAGE >> 4) + ACC * 512 + 2 * ((J) & 3)), dB + (((J) >> 2) * (G1_STAGE >> 4) + 64 * ((J) & 3)), 1)
        if (tid == 0) TSB(78);
        mbar_wait(bar + 8 * (B_FULL1 + 0), 0);
        if (tid == 0) TSB(59);
        wg_fence();
#pragma unroll
        for (int j = 0; j < REL; j++) G1_MMA(0, j);
        wg_commit();
        wg_wait<1>();
        if (elect) mbar_arrive(bar + 8 * B_R2FREE);
        wg_fence();
#pragma unroll
        for (int j = REL; j < 4; j++) G1_MMA(0, j);
#pragma unroll
        for (int j = 0; j < TLA; j++) G1_MMA(1, j);
        if (tid == 0) TSB(79);
        mbar_wait(bar + 8 * (B_FULL1 + 1), 1);
        if (tid == 0) TSB(60);
        wg_fence();
#pragma unroll
        for (int j = 4; j < 8; j++) G1_MMA(0, j);
        wg_commit();
#pragma unroll
        for (int j = TLA; j < TLA + 2; j++) G1_MMA(1, j);
        wg_commit();
        const uint32_t hd = sb + (w >> 1) * G1_STAGE + wg * 16384 + (w & 1) * 3072 + (lane & 7) * 64 + (((lane >> 3) ^ ((lane & 7) >> 1)) << 4);
        mbar_wait(bar + 8 * B_GATE, 0);
        wg_wait<1>();
        pin<96>(acc0);
        if (elect) TS(2 + wg);
        wg_fence();
        if (TLA + 2 < 8) G1_MMA(1, TLA + 2);
        glu_part<0>(acc0, hd);
        if (TLA + 3 < 8) G1_MMA(1, TLA + 3);
        glu_part<1>(acc0, hd);
        if (TLA + 4 < 8) G1_MMA(1, TLA + 4);
        glu_part<2>(acc0, hd);
        if (TLA + 5 < 8) G1_MMA(1, TLA + 5);
        glu_part<3>(acc0, hd);
        if (TLA + 6 < 8) G1_MMA(1, TLA + 6);
        glu_part<4>(acc0, hd);
        if (TLA + 7 < 8) G1_MMA(1, TLA + 7);
        wg_commit();
        glu_part<5>(acc0, hd);
        asm volatile("fence.proxy.async.shared::cta;" ::: "memory");
        __syncwarp();
        if (lane == 0) mbar_arrive(bar + 8 * (B_SIGH + 2 * wg));
        if (elect) TSB(6 + wg);
        const uint64_t ca = conv_da(wg), cb = conv_db(wg);
        mbar_wait(bar + 8 * (B_UFULL + wg), 0);
        if (elect) TS(10 + 3 * wg);
        wg_fence();
        conv_mma<0, CV0>(d0, ca, cb);
        wg_commit();
        wg_wait<1>();
        pin<96>(acc1);
        if (elect) mbar_arrive(bar + 8 * B_G1DONE);
        wg_fence();
        constexpr int gs[7] = {GL1};
        conv_mma<CV0 + gs[0], CV0 + gs[1]>(d0, ca, cb);
        glu_part<0>(acc1, hd + 8192);
        conv_mma<CV0 + gs[1], CV0 + gs[2]>(d0, ca, cb);
        glu_part<1>(acc1, hd + 8192);
        conv_mma<CV0 + gs[2], CV0 + gs[3]>(d0, ca, cb);
        glu_part<2>(acc1, hd + 8192);
        conv_mma<CV0 + gs[3], CV0 + gs[4]>(d0, ca, cb);
        glu_part<3>(acc1, hd + 8192);
        conv_mma<CV0 + gs[4], CV0 + gs[5]>(d0, ca, cb);
        glu_part<4>(acc1, hd + 8192);
        conv_mma<CV0 + gs[5], CV0 + gs[6]>(d0, ca, cb);
        glu_part<5>(acc1, hd + 8192);
        asm volatile("fence.proxy.async.shared::cta;" ::: "memory");
        __syncwarp();
        if (lane == 0) mbar_arrive(bar + 8 * (B_SIGH + 2 * wg + 1));
        if (elect) TS(4 + wg);
        conv_mma<CV0 + gs[6], 32>(d0, ca, cb);
        wg_commit();
      }
      {
        const uint64_t ca = conv_da(wg + 2), cb = conv_db(wg + 2);
        mbar_wait(bar + 8 * (B_UFULL + wg + 2), 0);
        if (elect) TS(16 + 3 * wg);
        wg_fence();
        conv_mma<0, CV0>(d1, ca, cb);
        wg_commit();
        wg_wait<1>();
        pin<64>(d0);
        if (elect) TSB(11 + 3 * wg);
        wg_fence();
        conv_finish<1>(d0, sb, bar, wg, wg, w, d1, ca, cb);
        if (elect) TS(12 + 3 * wg);
      }
      if (wg == 0) {
        const uint64_t ca = conv_da(4), cb = conv_db(4);
        mbar_wait(bar + 8 * (B_UFULL + 4), 0);
        if (elect) TS(22);
        wg_fence();
        conv_mma<0, CV0>(d0, ca, cb);
        wg_commit();
        wg_wait<1>();
        pin<64>(d1);
        if (elect) TSB(17);
        wg_fence();
        conv_finish<2>(d1, sb, bar, 2, wg, w, d0, ca, cb);
        if (elect) TS(18);
        wg_wait<0>();
        pin<64>(d0);
        if (elect) TS(23);
        conv_finish<0>(d0, sb, bar, 4, wg, w, d0, ca, cb);
        if (elect) TS(24);
      } else {
        wg_wait<0>();
        pin<64>(d1);
        if (elect) TS(20);
        conv_finish<0>(d1, sb, bar, 3, wg, w, d1, 0, 0);
        if (elect) TS(21);
      }
    }
    const int lane = fresh_lane();
    const uint32_t xo = w * 512 + lane * 16;
    if (wg == 1) {
      float accF[80], accO[80];
      const uint64_t dA = mkdesc(SB0, 1024, 1024, 1);
      const uint64_t dB = mkdesc(SB0, 16, 512, 2);
#define G2_STAGE(S)                                                              \
      if (elect) TS(80 + 4 * r + S);                                             \
      mbar_wait(bar + 8 * (B_FULL2 + S), r);                                     \
      if (elect) TS(64 + 4 * r + S);                                             \
      wg_fence();                                                                \
      g2_half<S, 0, 0, REL2>(accF, dA, dB, (r | S) != 0);                        \
      wg_commit();                                                               \
      wg_wait<1>();                                                              \
      if ((r | S) != 0 && elect) mbar_arrive(bar + 8 * (B_EMPTY2 + ((S + 3) & 3))); \
      wg_fence();                                                                \
      g2_half<S, 0, REL2, 4>(accF, dA, dB, 1);                                   \
      g2_half<S, 1>(accO, dA, dB, (r | S) != 0);                                 \
      wg_commit();
#pragma unroll 1
      for (int r = 0; r < 2; r++) {
        G2_STAGE(0) G2_STAGE(1) G2_STAGE(2) G2_STAGE(3)
      }
      mbar_wait(bar + 8 * (B_FULL2 + 0), 0);
      if (elect) TS(72);
      wg_fence();
      g2_half<0, 0, 0, REL2>(accF, dA, dB, 1);
      wg_commit();
      wg_wait<1>();
      if (elect) mbar_arrive(bar + 8 * (B_EMPTY2 + 3));
      wg_fence();
      g2_half<0, 0, REL2, 4>(accF, dA, dB, 1);
      g2_half<0, 1>(accO, dA, dB, 1);
      mbar_wait(bar + 8 * (B_FULL2 + 1), 0);
      if (elect) TS(73);
      wg_fence();
      g2_half<1, 0>(accF, dA, dB, 1);
      g2_half<1, 1, 0, TM9>(accO, dA, dB, 1);
      mbar_wait(bar + 8 * (B_FULL2 + 2), 0);
      if (elect) TS(74);
      wg_fence();
      g2_half<2, 0>(accF, dA, dB, 1);
      g2_half<1, 1, TM9, (TM10 < 4 ? TM10 : 4)>(accO, dA, dB, 1);
      g2_half<2, 1, 0, TM10 - 4>(accO, dA, dB, 1);
      mbar_wait(bar + 8 * B_XF, 0);
      mbar_wait(bar + 8 * (B_FULL2 + 3), 0);
      if (elect) TS(75);
      wg_fence();
      g2_half<3, 0>(accF, dA, dB, 1);
      wg_commit();
#define G2_OWN(I) do { if ((I) < 12) g2_half<(((I) >> 2) + 1) & 3, 1, (I) & 3, ((I) & 3) + 1>(accO, dA, dB, 1); } while (0)
      G2_OWN(TM10);
      G2_OWN(TM10 + 1);
      wg_commit();
      {
        const uint32_t xd = peer_addr(sb + OFF_XCH + xo), xb = peer_addr(bar + 8 * B_XCH);
        wg_wait<1>();
        pin<80>(accF);
        if (elect) TS(36);
        wg_fence();
#define G2_SEND(I)                                                                                                                                  \
        asm volatile("st.async.shared::cluster.mbarrier::complete_tx::bytes.v4.b32 [%0], {%1,%2,%3,%4}, [%5];" ::"r"(xd + (I) * 2048),              \
                     "r"(pack_bf16(accF[8 * (I)], accF[8 * (I) + 1])), "r"(pack_bf16(accF[8 * (I) + 2], accF[8 * (I) + 3])),                        \
                     "r"(pack_bf16(accF[8 * (I) + 4], accF[8 * (I) + 5])), "r"(pack_bf16(accF[8 * (I) + 6], accF[8 * (I) + 7])),                    \
                     "r"(xb + ((I) / 5) * 8) : "memory");                                                                                           \
        G2_OWN(TM10 + 2 + (I));
        G2_SEND(0) G2_SEND(1) G2_SEND(2) G2_SEND(3) G2_SEND(4) G2_SEND(5) G2_SEND(6) G2_SEND(7) G2_SEND(8) G2_SEND(9)
        wg_commit();
      }
      if (elect) TS(37);
      wg_wait<0>();
      pin<80>(accO);
      if (elect) TS(28);
#pragma unroll
      for (int i = 0; i < 10; i++) {
        asm volatile("st.shared.v4.b32 [%0], {%1,%2,%3,%4};" ::"r"(sb + slotB0(0) + xo + i * 2048), "r"(pack_bf16(accO[8 * i], accO[8 * i + 1])),
                     "r"(pack_bf16(accO[8 * i + 2], accO[8 * i + 3])), "r"(pack_bf16(accO[8 * i + 4], accO[8 * i + 5])),
                     "r"(pack_bf16(accO[8 * i + 6], accO[8 * i + 7])) : "memory");
        if (i % 5 == 4) bar_arrive(i < 5 ? 6 : 8, 256);
      }
      if (elect) TS(38);
    } else {
      const int q = lane & 3, i8 = lane & 7, mi = lane >> 3;
      const uint32_t qa = sb + OFF_Q + ((mi >> 1) * 8 + i8) * 128 + (((2 * w + (mi & 1)) ^ i8) << 4);
      const uint32_t za = sb + OFF_Z + (16 * w + (lane >> 2)) * 320 + q * 80;
      uint32_t qv[40], om[20];
      mbar_wait(bar + 8 * B_QG, 0);
#pragma unroll
      for (int jp = 0; jp < 10; jp++)
        asm volatile("ldmatrix.sync.aligned.m8n8.x4.trans.shared.b16 {%0,%1,%2,%3}, [%4];" : "=r"(qv[4 * jp]), "=r"(qv[4 * jp + 1]), "=r"(qv[4 * jp + 2]), "=r"(qv[4 * jp + 3]) : "r"(qa + jp * 2048) : "memory");
#pragma unroll
      for (int j = 0; j < 20; j++) {
        const uint32_t g2 = *reinterpret_cast<const uint32_t*>(sm + OFF_G + j * 32 + 4 * q);
        om[j] = *reinterpret_cast<const uint32_t*>(sm + OFF_G + j * 32 + 16 + 4 * q);
        qv[2 * j] = bmul2(qv[2 * j], g2);
        qv[2 * j + 1] = bmul2(qv[2 * j + 1], g2);
      }
#pragma unroll 1
      for (int pass = 0; pass < 2; pass++) {
        const uint32_t zp = pass ? za : sb, xp = pass ? xo : 0;
        if (elect) TS(60);
        if (pass) mbar_wait(bar + 8 * B_Z, 0);
        if (elect) TS(27);
        uint32_t av[40];
#pragma unroll
        for (int i = 0; i < 10; i++)
          asm volatile("ld.shared.v4.u32 {%0,%1,%2,%3}, [%4];" : "=r"(av[8 * (i >> 1) + (i & 1)]), "=r"(av[8 * (i >> 1) + 2 + (i & 1)]), "=r"(av[8 * (i >> 1) + 4 + (i & 1)]), "=r"(av[8 * (i >> 1) + 6 + (i & 1)])
                       : "r"(zp + (i & 1) * 2560 + (i >> 1) * 16) : "memory");
#pragma unroll
        for (int i = 0; i < 40; i++) av[i] = bmul2(av[i], qv[i]);
        if (elect) TS(29);
#pragma unroll
        for (int hf = 0; hf < 2; hf++) {
          uint32_t p[20], o[20];
          if (pass) mbar_wait(bar + 8 * (B_XCH + hf), 0);
          if (elect) TS(hf ? 59 : 31);
#pragma unroll
          for (int i = 0; i < 5; i++)
            asm volatile("ld.shared.v4.u32 {%0,%1,%2,%3}, [%4];" : "=r"(p[4 * i]), "=r"(p[4 * i + 1]), "=r"(p[4 * i + 2]), "=r"(p[4 * i + 3]) : "r"(sb + OFF_XCH + xp + (5 * hf + i) * 2048) : "memory");
          if (pass) bar_sync(hf ? 8 : 6, 256);
          if (elect) TS(hf ? 79 : 78);
#pragma unroll
          for (int i = 0; i < 5; i++)
            asm volatile("ld.shared.v4.u32 {%0,%1,%2,%3}, [%4];" : "=r"(o[4 * i]), "=r"(o[4 * i + 1]), "=r"(o[4 * i + 2]), "=r"(o[4 * i + 3]) : "r"(sb + slotB0(0) + xp + (5 * hf + i) * 2048) : "memory");
#pragma unroll
          for (int i = 0; i < 20; i++) o[i] = bfma2(badd2(o[i], p[i]), om[10 * hf + (i >> 1)], av[20 * hf + i]);
#pragma unroll
          for (int i = 0; i < 5; i++)
            asm volatile("{\n.reg .pred p;\nsetp.ne.u32 p, %5, 0;\n@p stmatrix.sync.aligned.m8n8.x4.trans.shared.b16 [%0], {%1,%2,%3,%4};\n}" ::"r"(qa + (5 * hf + i) * 2048), "r"(o[4 * i]), "r"(o[4 * i + 1]), "r"(o[4 * i + 2]), "r"(o[4 * i + 3]), "r"(pass) : "memory");
          asm volatile("fence.proxy.async.shared::cta;" ::: "memory");
          if (elect) TS(57 + hf);
          bar_sync(3, 128);
          if (pass && w == 0 && elect_one()) tma4_store(&mO, sb + OFF_Q + hf * 10240, db * 64, 0, ((2 * tb + hf) % 13) * 10, (2 * tb + hf) / 13);
        }
      }
      if (elect) TS(26);
      if (w == 0) {
        asm volatile("cp.async.bulk.commit_group;" ::: "memory");
        asm volatile("cp.async.bulk.wait_group.read 0;" ::: "memory");
      }
      if (elect) {
        TS(30);
      }
    }
  } else {
    asm volatile("setmaxnreg.dec.sync.aligned.u32 56;");
    if (warp == 8) {
      if (has1) {
#define KV_COPY()                                                                                    \
          tma3(sb + OFF_H, &mK, (cta & 7) * 80, (cta >> 3) * 16 - 2, 0, bar + 8 * B_KV);             \
          tma3(sb + OFF_V, &mV, (cta & 7) * 80, (cta >> 3) * 16 - 1, 0, bar + 8 * B_KV);             \
          bulk_g2s(sb + OFF_EX, P.shift_k + (cta & 7) * 320, 640, bar + 8 * B_KV);
        if (elect_one()) {
          KV_COPY();
        }
        float s[4] = {0.f, 0.f, 0.f, 0.f};
        const uint32_t xa = sb + ft * 2048 + (lane >> 3) * 128;
#pragma unroll 1
        for (int kb = 2; kb < 12; kb++) {
          const int kg = kb - 2, rg = (kb - 1) % 3;
          if (kb >= 3 && kb < 10) {
            const int rl = (kb + 1) % 3;
            const uint32_t dst = sb + rl * G1_STAGE, fb = bar + 8 * (B_FULL1 + rl);
            mbar_wait_t(bar + 8 * (B_EMPTY1 + rl), (kb / 3 - 1) & 1);
            if (elect_one()) {
              tma4(dst, &mX, kb * 64, 0, (mb & 3) * 32, mb >> 2, fb);
              tma3(dst + 32768, &mWg, 0, kb * 64, ft * 3, fb);
              tma3(dst + 32768 + 12288, &mWu, 0, kb * 64, ft * 3, fb);
              if (kb == KVAT) { KV_COPY(); }
              TS(85 + kb);
            }
          } else {
            mbar_wait_t(bar + 8 * (B_FULL1 + rg), (kg / 3) & 1);
          }
          uint4 xv[4], gw;
#pragma unroll
          for (int i = 0; i < 4; i++)
            asm volatile("ld.shared.v4.u32 {%0,%1,%2,%3}, [%4];" : "=r"(xv[i].x), "=r"(xv[i].y), "=r"(xv[i].z), "=r"(xv[i].w)
                         : "r"(xa + rg * G1_STAGE + i * 512 + (((lane & 7) ^ ((lane >> 3) + 4 * (i & 1))) << 4)) : "memory");
          asm volatile("ld.shared.v4.u32 {%0,%1,%2,%3}, [%4];" : "=r"(gw.x), "=r"(gw.y), "=r"(gw.z), "=r"(gw.w) : "r"(sb + OFF_EX + 640 + kg * 128 + (lane & 7) * 16) : "memory");
          if (lane == 0 && kg < 7) mbar_expect(bar + 8 * (B_FULL1 + rg), G1_STAGE);
          if (kb == PFK && elect_one()) bulk_prefetch(P.ssm_k + (size_t)cta * 5 * 2048, 20480);
          if (kb == PFW && elect_one()) bulk_prefetch(P.w_down + (size_t)cta * 7680, 15360);
#pragma unroll
          for (int i = 0; i < 4; i++) {
            const uint32_t p0 = bmul2(xv[i].x, gw.x), p1 = bmul2(xv[i].y, gw.y), p2 = bmul2(xv[i].z, gw.z), p3 = bmul2(xv[i].w, gw.w);
            s[i] += (bflo(p0) + bfhi(p0)) + (bflo(p1) + bfhi(p1)) + ((bflo(p2) + bfhi(p2)) + (bflo(p3) + bfhi(p3)));
          }
          pin<4>(s);
          __syncwarp();
          if (kg == 7 && lane == 0) mbar_arrive(bar + 8 * B_R2FREE);
        }
        if (lane == 0) { mbar_arrive(bar + 8 * B_GATE); TS(44); }
        float s0 = (lane & 4) ? s[2] : s[0], s1 = (lane & 4) ? s[3] : s[1];
        s0 += __shfl_xor_sync(0xffffffffu, (lane & 4) ? s[0] : s[2], 4);
        s1 += __shfl_xor_sync(0xffffffffu, (lane & 4) ? s[1] : s[3], 4);
        float sv = (lane & 2) ? s1 : s0;
        sv += __shfl_xor_sync(0xffffffffu, (lane & 2) ? s0 : s1, 2);
        sv += __shfl_xor_sync(0xffffffffu, sv, 1);
        sv = __bfloat162float(__float2bfloat16(sv));
        sv = __bfloat162float(__float2bfloat16(1.f / (1.f + __expf(-sv))));
        reinterpret_cast<__nv_bfloat16*>(sm + OFF_GS)[(lane & 4) * 4 + (lane & 1) * 8 + (lane & 2) * 2 + (lane >> 3)] = __float2bfloat16((lane & 1) ? 0.5f - 0.5f * sv : sv);
        asm volatile("fence.proxy.async.shared::cta;" ::: "memory");
        __syncwarp();
        if (lane == 0) mbar_arrive(bar + 8 * B_GS);
        mbar_wait_t(bar + 8 * B_R2FREE, 0);
      }
#pragma unroll 1
      for (int r = 0; r < 3; r++) {
#pragma unroll
        for (int s = 0; s < 4; s++) {
          const uint32_t fb = bar + 8 * (B_FULL2 + s);
          if (r) mbar_wait_t(bar + 8 * (B_EMPTY2 + s), r >> 1);
          else if (s == 1 && has1) mbar_wait_t(bar + 8 * B_G1DONE, 0);
          if (elect_one()) {
            mbar_expect(fb, 36864);
            tma3(sb + slotF(s), &mWd, 0, rank * 768 + r * 256 + s * 64, db ^ 1, fb);
            tma3(sb + slotO(s), &mWd, 0, rank * 768 + r * 256 + s * 64, db, fb);
            TS(96 + 4 * r + s);
          }
        }
      }
    } else {
      const int hw = warp - 9;
      if ((sb & 0x3FFFF) != SB0) __trap();
      if (hw == 2) asm volatile("barrier.cluster.arrive.release.aligned;\nbarrier.cluster.wait.acquire.aligned;" ::: "memory");
      if (has1) {
      {
        const int cq = lane & 3, gl = hw < 2 ? hw * 8 + ((lane >> 2) ^ ((cq & 2) << 1)) + 1 : 0;
        const int cl = hw < 2 ? 0 : lane >> 2;
        uint32_t kp = sb + OFF_H + gl * 160 + cq * 8 + cl * 32, wp = sb + OFF_EX + cq * 32 + cl * 128;
        const uint32_t u1 = sb + OFF_US + cq * 2048 + (15 - gl) * 16, u2 = u1 + 24;
        const uint32_t ua = (cq & 1) && hw < 2 ? u2 : u1, ub = (cq & 1) ? u1 : u2;
        const bool pa0 = (cq & 1) || gl <= 15, pb0 = !(cq & 1) || gl <= 15;
        uint2 vr[8], kr[11];
        uint4 sa, sc;
#define KV_LOAD_K()                                                                                                                                   \
        asm volatile("ld.volatile.shared.v4.u32 {%0,%1,%2,%3}, [%4];" : "=r"(sa.x), "=r"(sa.y), "=r"(sa.z), "=r"(sa.w) : "r"(wp) : "memory");       \
        asm volatile("ld.volatile.shared.v4.u32 {%0,%1,%2,%3}, [%4];" : "=r"(sc.x), "=r"(sc.y), "=r"(sc.z), "=r"(sc.w) : "r"(wp + 16) : "memory");  \
        _Pragma("unroll") for (int r = 0; r < 3; r++) kr[r] = lds64(kp + (r + 5) * 18 * 160);                                                        \
        _Pragma("unroll") for (int r = 0; r < KVA; r++) kr[r + 3] = lds64(kp + (r * 18 + 1) * 160);
#define KV_LOAD_V()                                                                                                                                   \
        _Pragma("unroll") for (int r = KVA; r < 8; r++) kr[r + 3] = lds64(kp + (r * 18 + 1) * 160);                                                  \
        _Pragma("unroll") for (int r = 0; r < KVB; r++) vr[r] = lds64(kp + 23040 + r * 17 * 160);
#define KV_COMPUTE()                                                                                                                                  \
        {                                                                                                                                             \
          const uint32_t wa[4] = {__byte_perm(sa.x, sa.z, 0x5410), __byte_perm(sa.x, sa.z, 0x7632), __byte_perm(sa.y, sa.w, 0x5410), __byte_perm(sa.y, sa.w, 0x7632)}; \
          const uint32_t wb[4] = {__byte_perm(sc.x, sc.z, 0x5410), __byte_perm(sc.x, sc.z, 0x7632), __byte_perm(sc.y, sc.w, 0x5410), __byte_perm(sc.y, sc.w, 0x7632)}; \
          _Pragma("unroll") for (int r = 0; r < 8; r++) {                                                                                             \
            uint32_t x = bmul2(kr[r].x, wa[3]), y = bmul2(kr[r].y, wb[3]);                                                                            \
            if (r + KVB < 8) vr[r + KVB] = lds64(kp + 23040 + (r + KVB) * 17 * 160);                                                                  \
            _Pragma("unroll") for (int j = 1; j < 4; j++) {                                                                                           \
              x = bfma2(kr[r + j].x, wa[3 - j], x);                                                                                                   \
              y = bfma2(kr[r + j].y, wb[3 - j], y);                                                                                                   \
            }                                                                                                                                         \
            vr[r].x = bmul2(x, vr[r].x);                                                                                                              \
            vr[r].y = bmul2(y, vr[r].y);                                                                                                              \
          }                                                                                                                                           \
        }
#define KV_STORE(PA, PB)                                                                                                                              \
        _Pragma("unroll") for (int cc = 0; cc < 4; cc++) {                                                                                            \
          const uint32_t sel = (cc & 1) ? 0x7632 : 0x5410;                                                                                            \
          _Pragma("unroll") for (int p = 0; p < 2; p++) {                                                                                             \
            const int r = 4 - 4 * p;                                                                                                                  \
            const uint32_t qx = (cc & 2) ? __byte_perm(vr[r].y, vr[r + 1].y, sel) : __byte_perm(vr[r].x, vr[r + 1].x, sel);                           \
            const uint32_t qy = (cc & 2) ? __byte_perm(vr[r + 2].y, vr[r + 3].y, sel) : __byte_perm(vr[r + 2].x, vr[r + 3].x, sel);                   \
            if (PA) asm volatile("st.shared.v2.u32 [%0], {%1,%2};" ::"r"(ua + cc * 512 + p * 256), "r"(qx), "r"(qy) : "memory");                      \
            if (PB) asm volatile("st.shared.v2.u32 [%0], {%1,%2};" ::"r"(ub + cc * 512 + p * 256), "r"(qx), "r"(qy) : "memory");                      \
          }                                                                                                                                           \
        }                                                                                                                                             \
        asm volatile("fence.proxy.async.shared::cta;" ::: "memory");
        mbar_wait_t(bar + 8 * B_KV, 0);
        if (hw == 0 && lane == 0) TS(39);
        KV_LOAD_K();
        KV_LOAD_V();
        if (hw < 2) {
#pragma unroll 1
          for (int cb = 0; cb < 5; cb++) {
            if (cb == 2 && lane == 0) TS(108);
            KV_COMPUTE();
            kp += 32;
            wp += 128;
            KV_LOAD_K();
            if (cb == 2 && lane == 0) TS(109);
            bar_sync(5, 96);
            if (cb == 2 && lane == 0) TS(110);
            KV_STORE(pa0, pb0);
            if (cb == 2 && lane == 0) TS(111);
            KV_LOAD_V();
            __syncwarp();
            bar_arrive(7, 96);
            if (cb == 2 && lane == 0) TS(9);
          }
        } else {
          KV_COMPUTE();
#pragma unroll 1
          for (int cb = 0; cb < 5; cb++) {
            asm volatile("cp.async.bulk.wait_group.read 0;" ::: "memory");
            bar_sync(5, 96);
            if (cb == 4 && elect_one()) {
              mbar_expect(bar + 8 * B_HLD, 20480);
#pragma unroll
              for (int ch = 0; ch < 5; ch++)
                bulk_g2s(sb + OFF_H + (2 * ch + 1) * H_PITCH + 224, P.ssm_k + (size_t)(cta * 5 + ch) * 2048, 4096, bar + 8 * B_HLD);
            }
            KV_STORE(cl == cb, false);
            __syncwarp();
            bar_sync(7, 96);
            if (elect_one()) tma2_store(&mU, sb + OFF_US, 1920 - 128 * (cta >> 3), (cta & 7) * 160 + cb * 32);
            asm volatile("cp.async.bulk.commit_group;" ::: "memory");
          }
        }
        if (lane == 0) TS(54 + hw);
        if (hw == 2) {
          asm volatile("cp.async.bulk.wait_group 0;" ::: "memory");
          __syncwarp();
          if (lane == 0) { flag_add(&g_cnt[(C_U + (cta & 7)) * 32]); TS(40); }
          flag_wait(&g_cnt[(C_U + mb) * 32], &g_cnt[(C_U + mb) * 32], 16);
          if (lane == 0) TS(32);
          mbar_wait_t(bar + 8 * B_R2FREE, 0);
          if (elect_one()) {
#pragma unroll
            for (int ch = 0; ch < 5; ch++) {
              mbar_expect(bar + 8 * (B_UFULL + ch), 8192);
              bulk_g2s(sb + OFF_U + (4 - ch) * 8192, g_U + (size_t)(5 * cta + ch) * 4096, 8192, bar + 8 * (B_UFULL + ch));
            }
            TS(33);
          }
        }
      }
      if (hw < 2) {
        const int ht = tid - 288;
        for (int i = ht; i < 10 * 15; i += 64) {
          const int b = i / 15, e = i % 15;
          if (e < 14) *reinterpret_cast<uint4*>(sm + OFF_H + b * H_PITCH + e * 16) = make_uint4(0u, 0u, 0u, 0u);
          else if ((b & 1) == 0) *reinterpret_cast<uint2*>(sm + OFF_H + b * H_PITCH + 224) = make_uint2(0u, 0u);
        }
        const float dv = lane < 5 ? __bfloat162float(P.ssm_D[cta * 5 + lane]) : 0.f;
        __syncwarp();
        mbar_wait_t(bar + 8 * B_HLD, 0);
        if (hw == 0) {
          if (lane < 5) {
            __nv_bfloat16* h0 = reinterpret_cast<__nv_bfloat16*>(sm + OFF_H + (2 * lane + 1) * H_PITCH + 224);
            *h0 = __float2bfloat16(__bfloat162float(*h0) + dv);
          }
          __syncwarp();
        }
#pragma unroll 1
        for (int b = 0; b < 5; b++) {
          unsigned char* dst = sm + OFF_H + b * 2 * H_PITCH + hw * 2048 + 232 + lane * 8;
          uint2 hv[8];
#pragma unroll
          for (int u = 0; u < 8; u++) hv[u] = *reinterpret_cast<const uint2*>(dst + H_PITCH - 8 + u * 256);
#pragma unroll
          for (int u = 0; u < 8; u++) *reinterpret_cast<uint2*>(dst + u * 256) = hv[u];
          asm volatile("fence.proxy.async.shared::cta;" ::: "memory");
          __syncwarp();
          if (lane == 0) mbar_arrive(bar + 8 * (B_UFULL + b));
        }
        if (hw == 1 && lane == 0) TS(41);
      }
      }
      const int ga = 20 * tb, gb = ga + 19;
      const unsigned* fa = &g_cnt[(C_H + 2 * ((ga / 130) * 4 + min((ga % 130) >> 5, 3))) * 32];
      const unsigned* fb = &g_cnt[(C_H + 2 * ((gb / 130) * 4 + min((gb % 130) >> 5, 3))) * 32];
      if (hw == 0) {
        const __nv_bfloat16* hsrc = g_Hs + (size_t)(rank * 24 * NGRP + ga) * 256;
        if (has1) mbar_wait_t(bar + 8 * B_HDR, 0);
        if (lane == 0) TS(25);
        flag_wait(fa + rank * 32, fb + rank * 32, 8);
        if (lane == 0) TS(34);
#pragma unroll 1
        for (int r = 0; r < 3; r++) {
#pragma unroll
          for (int s = 0; s < 4; s++) {
            if (r) mbar_wait_t(bar + 8 * (B_EMPTY2 + s), r >> 1);
            else if (s == 3 && has1) { mbar_wait_t(bar + 8 * (B_CD + 0), 0); mbar_wait_t(bar + 8 * (B_CD + 1), 0); }
            if (elect_one()) {
              bulk_g2s(sb + slotB0(s), hsrc + s * (2 * NGRP * 256), 10240, bar + 8 * (B_FULL2 + s));
              bulk_g2s(sb + slotB1(s), hsrc + s * (2 * NGRP * 256) + NGRP * 256, 10240, bar + 8 * (B_FULL2 + s));
              TS(112 + 4 * r + s);
            }
          }
          hsrc += 8 * NGRP * 256;
        }
      } else if (hw == 1) {
        if (elect_one()) { prefetch_map(&mQ); prefetch_map(&mZ); prefetch_map(&mO); }
        if (has1) for (int ch = 0; ch < 3; ch++) mbar_wait_t(bar + 8 * (B_CD + ch), 0);
        if (elect_one()) {
          mbar_expect(bar + 8 * B_QG, 20480 + 640);
#pragma unroll
          for (int hf = 0; hf < 2; hf++)
            tma4(sb + OFF_Q + hf * 10240, &mQ, db * 64, 0, ((2 * tb + hf) % 13) * 10, (2 * tb + hf) / 13, bar + 8 * B_QG);
        }
        flag_wait(fa, fb, 8);
        flag_wait(fa + 32, fb + 32, 8);
        if (elect_one()) {
          bulk_g2s(sb + OFF_G, g_gate + ga * 8, 640, bar + 8 * B_QG);
          mbar_expect(bar + 8 * B_Z, 20480);
        }
        if (has1) { mbar_wait_t(bar + 8 * (B_CD + 3), 0); mbar_wait_t(bar + 8 * (B_CD + 4), 0); }
        flag_wait(&g_cnt[(C_Z + db) * 32], &g_cnt[(C_Z + db) * 32], (64 * db + 63) / 5 - (64 * db) / 5 + 1);
        if (elect_one()) { tma2(sb + OFF_Z, &mZ, tb * 160, db * 64, bar + 8 * B_Z); TS(35); }
        mbar_wait_t(bar + 8 * (B_FULL2 + 0), 0);
        if (lane == 0 && atomicAdd(&g_cnt[C_DONE * 32], 1u) == NCTA - 1) {
          for (int i = 0; i < C_COUNT; i++) g_cnt[i * 32] = 0;
        }
      } else {
        if (has1) {
          const int g0 = (mb >> 2) * 130 + (mb & 3) * 32;
          mbar_wait_t(bar + 8 * B_GS, 0);
          if (elect_one()) bulk_s2g(g_gate + (g0 + 2 * ft) * 8, sb + OFF_GS, 64);
#pragma unroll 1
          for (int j = 0; j < 4; j++) {
            const int i = (j >> 1) | ((j & 1) << 1);
            mbar_wait_t(bar + 8 * (B_SIGH + i), 0);
            if (elect_one()) {
              tma3_store(&mH, sb + i * 8192, 0, 3 * ft, g0 + 8 * i);
              tma3_store(&mH, sb + G1_STAGE + i * 8192, 0, 3 * ft, g0 + 8 * i + 4);
            }
          }
          asm volatile("cp.async.bulk.commit_group;" ::: "memory");
          asm volatile("cp.async.bulk.wait_group.read 0;" ::: "memory");
          __syncwarp();
          if (lane == 0) { mbar_arrive(bar + 8 * B_HDR); TS(45); }
          asm volatile("cp.async.bulk.wait_group 0;" ::: "memory");
          __syncwarp();
          if (lane == 0) { flag_add(&g_cnt[(C_H + 2 * mb + (ft >> 3)) * 32]); TS(42); }
#pragma unroll 1
          for (int ch = 0; ch < 5; ch++) {
            __nv_bfloat16* zd = g_zT + (size_t)(5 * cta + ch) * (NGRP * 8);
            mbar_wait_t(bar + 8 * (B_SIGZ + ch), 0);
            if (elect_one()) bulk_s2g(zd, sb + zstage(ch), NGRP * 16);
          }
          asm volatile("cp.async.bulk.commit_group;" ::: "memory");
          asm volatile("cp.async.bulk.wait_group 0;" ::: "memory");
          __syncwarp();
          if (lane == 0) flag_add(&g_cnt[(C_Z + (5 * cta) / 64) * 32]);
          if (lane == 0 && (5 * cta) / 64 != (5 * cta + 4) / 64) flag_add(&g_cnt[(C_Z + (5 * cta + 4) / 64) * 32]);
          if (lane == 0) TS(43);
        }
        if (lane == 0) asm volatile("mbarrier.arrive.relaxed.cluster.shared::cluster.b64 _, [%0];" ::"r"(peer_addr(bar + 8 * B_XF)) : "memory");
      }
    }
  }
}

typedef CUresult (*EncFn)(CUtensorMap*, CUtensorMapDataType, cuuint32_t, void*, const cuuint64_t*, const cuuint64_t*,
                          const cuuint32_t*, const cuuint32_t*, CUtensorMapInterleave, CUtensorMapSwizzle,
                          CUtensorMapL2promotion, CUtensorMapFloatOOBfill);

void make_map(EncFn enc, CUtensorMap* m, const void* ptr, int rank, const cuuint64_t* dims, const cuuint64_t* str,
              const cuuint32_t* box, CUtensorMapSwizzle sw) {
  const cuuint32_t es[5] = {1, 1, 1, 1, 1};
  enc(m, CU_TENSOR_MAP_DATA_TYPE_BFLOAT16, rank, const_cast<void*>(ptr), dims, str, box, es, CU_TENSOR_MAP_INTERLEAVE_NONE,
      sw, CU_TENSOR_MAP_L2_PROMOTION_L2_128B, CU_TENSOR_MAP_FLOAT_OOB_FILL_NONE);
}

__global__ void probe_kernel() {}

void cluster_order(unsigned char* perm) {
  constexpr int NP = NCTA / 2;
  for (int c = 0; c < NP; c++) perm[c] = c;
  int n[9] = {0};
  cudaFuncSetAttribute(probe_kernel, cudaFuncAttributeMaxDynamicSharedMemorySize, SMEM_BYTES);
  cudaFuncSetAttribute(probe_kernel, cudaFuncAttributeNonPortableClusterSizeAllowed, 1);
  for (int k = 1; k <= 8; k++) {
    cudaLaunchConfig_t cfg = {};
    cudaLaunchAttribute at;
    at.id = cudaLaunchAttributeClusterDimension;
    at.val.clusterDim.x = 2 * k; at.val.clusterDim.y = 1; at.val.clusterDim.z = 1;
    cfg.gridDim = dim3(16 * k); cfg.blockDim = dim3(384); cfg.dynamicSmemBytes = SMEM_BYTES;
    cfg.attrs = &at; cfg.numAttrs = 1;
    if (cudaOccupancyMaxActiveClusters(&n[k], probe_kernel, &cfg) != cudaSuccess) { cudaGetLastError(); return; }
  }
  int R[9];
  R[7] = n[8]; R[6] = n[7]; R[5] = n[6]; R[4] = n[5]; R[3] = n[4] - n[8];
  R[0] = R[1] = R[2] = n[2] - R[3] - R[5] - R[7];
  R[8] = n[3] - R[2] - R[5];
  int lone = n[1];
  for (int r = 0; r < 9; r++) {
    if (R[r] < 0 || R[r] > 16 || (r && R[r] > R[r - 1])) return;
    lone -= R[r];
  }
  if (lone < 0 || n[1] < NP) return;
  int gpc[NP], rnd[NP];
  for (int c = 0, r = 0, pos = 0; c < NP; c++) {
    if (c < lone) { gpc[c] = -1; rnd[c] = 8; continue; }
    while (pos >= R[r]) { pos = 0; r++; }
    gpc[c] = R[0] - R[r] + pos++; rnd[c] = r;
  }
  int m = 0;
  for (int g = R[0] - 1; g >= 0; g--)
    for (int c = 0; c < NP; c++) if (gpc[c] == g && rnd[c] < 8) perm[c] = m++;
  for (int c = NP - 1; c >= 0; c--) if (rnd[c] == 8) perm[c] = m++;
}

}

extern "C" void kernel_launch(void* const* d_in, const int* in_sizes, int n_in, void* d_out, int out_size) {
  (void)in_sizes; (void)n_in; (void)out_size;
  static EncFn enc = nullptr;
  static unsigned char perm[NCTA / 2];
  static void *zT = nullptr, *uT = nullptr, *hT = nullptr;
  if (!enc) {
    cudaDriverEntryPointQueryResult qr;
    cudaGetDriverEntryPoint("cuTensorMapEncodeTiled", (void**)&enc, cudaEnableDefault, &qr);
    cudaGetSymbolAddress(&zT, g_zT);
    cudaGetSymbolAddress(&uT, g_U);
    cudaGetSymbolAddress(&hT, g_Hs);
    cudaFuncSetAttribute(fused_kernel, cudaFuncAttributeMaxDynamicSharedMemorySize, SMEM_BYTES);
    cluster_order(perm);
  }
  CUtensorMap mX, mWg, mWu, mWd, mQ, mZ, mO, mK, mV, mU, mH;
  {
    const cuuint64_t dims[4] = {640, 8, 128, 2}, str[3] = {128 * 1280, 1280, 1024 * 1280};
    const cuuint32_t b1[4] = {64, 8, 32, 1}, b2[4] = {64, 8, 10, 1};
    make_map(enc, &mX, d_in[0], 4, dims, str, b1, CU_TENSOR_MAP_SWIZZLE_128B);
    make_map(enc, &mQ, d_in[0], 4, dims, str, b2, CU_TENSOR_MAP_SWIZZLE_128B);
    make_map(enc, &mO, d_out, 4, dims, str, b2, CU_TENSOR_MAP_SWIZZLE_128B);
  }
  {
    const cuuint64_t dims[3] = {32, 640, 48}, str[2] = {3072, 64};
    const cuuint32_t box[3] = {32, 64, 3};
    make_map(enc, &mWg, d_in[7], 3, dims, str, box, CU_TENSOR_MAP_SWIZZLE_64B);
    make_map(enc, &mWu, d_in[8], 3, dims, str, box, CU_TENSOR_MAP_SWIZZLE_64B);
  }
  {
    const cuuint64_t dims[3] = {64, 1536, 10}, str[2] = {1280, 128};
    const cuuint32_t box[3] = {64, 64, 1};
    make_map(enc, &mWd, d_in[9], 3, dims, str, box, CU_TENSOR_MAP_SWIZZLE_128B);
  }
  {
    const cuuint64_t dims[2] = {NGRP * 8, 640}, str[1] = {NGRP * 16};
    const cuuint32_t box[2] = {160, 64};
    make_map(enc, &mZ, zT, 2, dims, str, box, CU_TENSOR_MAP_SWIZZLE_NONE);
  }
  {
    const cuuint64_t dims[3] = {256, 48, NGRP}, str[2] = {NGRP * 512, 512};
    const cuuint32_t box[3] = {256, 3, 4};
    make_map(enc, &mH, hT, 3, dims, str, box, CU_TENSOR_MAP_SWIZZLE_NONE);
  }
  {
    const cuuint64_t dims[3] = {640, 256, 8}, str[2] = {8 * 1280, 1280};
    const cuuint32_t bk[3] = {80, 18, 8}, bv[3] = {80, 17, 8};
    make_map(enc, &mK, d_in[1], 3, dims, str, bk, CU_TENSOR_MAP_SWIZZLE_NONE);
    make_map(enc, &mV, d_in[2], 3, dims, str, bv, CU_TENSOR_MAP_SWIZZLE_NONE);
  }
  {
    const cuuint64_t dims[2] = {2048, 1280}, str[1] = {4096};
    const cuuint32_t box[2] = {128, 32};
    make_map(enc, &mU, uT, 2, dims, str, box, CU_TENSOR_MAP_SWIZZLE_NONE);
  }
  Params P;
  P.q = (const __nv_bfloat16*)d_in[0]; P.k = (const __nv_bfloat16*)d_in[1]; P.v = (const __nv_bfloat16*)d_in[2];
  P.w_gate = (const __nv_bfloat16*)d_in[7]; P.w_up = (const __nv_bfloat16*)d_in[8]; P.w_down = (const __nv_bfloat16*)d_in[9];
  P.shift_k = (const __nv_bfloat16*)d_in[3]; P.ssm_k = (const __nv_bfloat16*)d_in[4]; P.ssm_D = (const __nv_bfloat16*)d_in[5];
  P.gate_w = (const __nv_bfloat16*)d_in[10];
  for (int c = 0; c < 65; c++) P.perm[c] = perm[c];
  fused_kernel<<<NCTA, 384, SMEM_BYTES>>>(mX, mWg, mWu, mWd, mQ, mZ, mO, mK, mV, mU, mH, P);
}
```

```cpp
#include <cuda_runtime.h>
#include <cuda.h>
#include <cuda_bf16.h>
#include <stdint.h>

namespace {
#define TM8 0
#define TM9 0
#define TM10 0
#define GMAP 1
#define G1MAP 1
#define REL 2
#define TLA 2
#define CV0 3
#define CV4S 0
#define CV4 0, 4, 8, 12, 16, 22, 26, 29
#define GL1S 0
#define GL1 0, 2, 4, 6, 8, 11, 14
#define G1SB sb
#define KVAT 0
#define KVPF 2
#define KVA 0
#define KVB 2
#define REL2 3
#define PFS 0
#define PFKV 0
#define PFM 0
#define PFL(p) asm volatile("prefetch.global.L2 [%0];" ::"l"(p) : "memory")
#define PFS3 0
#define PF0 3
#define PFD 0
#define PFD2 0
#define VAT 3
#define FCP 0
#define S0M 0
#define VPF 0
#define TAIL 1
#define KVX 0
#define KVXM 0
#define KVX_AT(i) do { if ((KVX >> (i)) & 1) __syncwarp(); } while (0)
#define SPN 1
#define SPD 1
#define AVL 2
#define P1E 0
#define KVTS 2
#define KVLD 0
#define KVW 1
#define C4ALL 0
#define PFK 4
#define PFW 6

template<int TA, int TB> __device__ __forceinline__ void wgmma_n8(float* d, uint64_t da, uint64_t db, int sc) {
  asm volatile("{\n.reg .pred p;\nsetp.ne.b32 p, %6, 0;\n"
    "wgmma.mma_async.sync.aligned.m64n8k16.f32.bf16.bf16 {%0, %1, %2, %3}, %4, %5, p, 1, 1, %7, %8;\n}\n"
    : "+f"(d[0]), "+f"(d[1]), "+f"(d[2]), "+f"(d[3])
    : "l"(da), "l"(db), "r"(sc), "n"(TA), "n"(TB));
}
template<int TA, int TB> __device__ __forceinline__ void wgmma_n16(float* d, uint64_t da, uint64_t db, int sc) {
  asm volatile("{\n.reg .pred p;\nsetp.ne.b32 p, %10, 0;\n"
    "wgmma.mma_async.sync.aligned.m64n16k16.f32.bf16.bf16 {%0, %1, %2, %3, %4, %5, %6, %7}, %8, %9, p, 1, 1, %11, %12;\n}\n"
    : "+f"(d[0]), "+f"(d[1]), "+f"(d[2]), "+f"(d[3]), "+f"(d[4]), "+f"(d[5]), "+f"(d[6]), "+f"(d[7])
    : "l"(da), "l"(db), "r"(sc), "n"(TA), "n"(TB));
}
template<int TA, int TB> __device__ __forceinline__ void wgmma_n24(float* d, uint64_t da, uint64_t db, int sc) {
  asm volatile("{\n.reg .pred p;\nsetp.ne.b32 p, %14, 0;\n"
    "wgmma.mma_async.sync.aligned.m64n24k16.f32.bf16.bf16 {%0, %1, %2, %3, %4, %5, %6, %7, %8, %9, %10, %11}, %12, %13, p, 1, 1, %15, %16;\n}\n"
    : "+f"(d[0]), "+f"(d[1]), "+f"(d[2]), "+f"(d[3]), "+f"(d[4]), "+f"(d[5]), "+f"(d[6]), "+f"(d[7]), "+f"(d[8]), "+f"(d[9]), "+f"(d[10]), "+f"(d[11])
    : "l"(da), "l"(db), "r"(sc), "n"(TA), "n"(TB));
}
template<int TA, int TB> __device__ __forceinline__ void wgmma_n32(float* d, uint64_t da, uint64_t db, int sc) {
  asm volatile("{\n.reg .pred p;\nsetp.ne.b32 p, %18, 0;\n"
    "wgmma.mma_async.sync.aligned.m64n32k16.f32.bf16.bf16 {%0, %1, %2, %3, %4, %5, %6, %7, %8, %9, %10, %11, %12, %13, %14, %15}, %16, %17, p, 1, 1, %19, %20;\n}\n"
    : "+f"(d[0]), "+f"(d[1]), "+f"(d[2]), "+f"(d[3]), "+f"(d[4]), "+f"(d[5]), "+f"(d[6]), "+f"(d[7]), "+f"(d[8]), "+f"(d[9]), "+f"(d[10]), "+f"(d[11]), "+f"(d[12]), "+f"(d[13]), "+f"(d[14]), "+f"(d[15])
    : "l"(da), "l"(db), "r"(sc), "n"(TA), "n"(TB));
}
template<int TA, int TB> __device__ __forceinline__ void wgmma_n40(float* d, uint64_t da, uint64_t db, int sc) {
  asm volatile("{\n.reg .pred p;\nsetp.ne.b32 p, %22, 0;\n"
    "wgmma.mma_async.sync.aligned.m64n40k16.f32.bf16.bf16 {%0, %1, %2, %3, %4, %5, %6, %7, %8, %9, %10, %11, %12, %13, %14, %15, %16, %17, %18, %19}, %20, %21, p, 1, 1, %23, %24;\n}\n"
    : "+f"(d[0]), "+f"(d[1]), "+f"(d[2]), "+f"(d[3]), "+f"(d[4]), "+f"(d[5]), "+f"(d[6]), "+f"(d[7]), "+f"(d[8]), "+f"(d[9]), "+f"(d[10]), "+f"(d[11]), "+f"(d[12]), "+f"(d[13]), "+f"(d[14]), "+f"(d[15]), "+f"(d[16]), "+f"(d[17]), "+f"(d[18]), "+f"(d[19])
    : "l"(da), "l"(db), "r"(sc), "n"(TA), "n"(TB));
}
template<int TA, int TB> __device__ __forceinline__ void wgmma_n48(float* d, uint64_t da, uint64_t db, int sc) {
  asm volatile("{\n.reg .pred p;\nsetp.ne.b32 p, %26, 0;\n"
    "wgmma.mma_async.sync.aligned.m64n48k16.f32.bf16.bf16 {%0, %1, %2, %3, %4, %5, %6, %7, %8, %9, %10, %11, %12, %13, %14, %15, %16, %17, %18, %19, %20, %21, %22, %23}, %24, %25, p, 1, 1, %27, %28;\n}\n"
    : "+f"(d[0]), "+f"(d[1]), "+f"(d[2]), "+f"(d[3]), "+f"(d[4]), "+f"(d[5]), "+f"(d[6]), "+f"(d[7]), "+f"(d[8]), "+f"(d[9]), "+f"(d[10]), "+f"(d[11]), "+f"(d[12]), "+f"(d[13]), "+f"(d[14]), "+f"(d[15]), "+f"(d[16]), "+f"(d[17]), "+f"(d[18]), "+f"(d[19]), "+f"(d[20]), "+f"(d[21]), "+f"(d[22]), "+f"(d[23])
    : "l"(da), "l"(db), "r"(sc), "n"(TA), "n"(TB));
}
template<int TA, int TB> __device__ __forceinline__ void wgmma_n56(float* d, uint64_t da, uint64_t db, int sc) {
  asm volatile("{\n.reg .pred p;\nsetp.ne.b32 p, %30, 0;\n"
    "wgmma.mma_async.sync.aligned.m64n56k16.f32.bf16.bf16 {%0, %1, %2, %3, %4, %5, %6, %7, %8, %9, %10, %11, %12, %13, %14, %15, %16, %17, %18, %19, %20, %21, %22, %23, %24, %25, %26, %27}, %28, %29, p, 1, 1, %31, %32;\n}\n"
    : "+f"(d[0]), "+f"(d[1]), "+f"(d[2]), "+f"(d[3]), "+f"(d[4]), "+f"(d[5]), "+f"(d[6]), "+f"(d[7]), "+f"(d[8]), "+f"(d[9]), "+f"(d[10]), "+f"(d[11]), "+f"(d[12]), "+f"(d[13]), "+f"(d[14]), "+f"(d[15]), "+f"(d[16]), "+f"(d[17]), "+f"(d[18]), "+f"(d[19]), "+f"(d[20]), "+f"(d[21]), "+f"(d[22]), "+f"(d[23]), "+f"(d[24]), "+f"(d[25]), "+f"(d[26]), "+f"(d[27])
    : "l"(da), "l"(db), "r"(sc), "n"(TA), "n"(TB));
}
template<int TA, int TB> __device__ __forceinline__ void wgmma_n64(float* d, uint64_t da, uint64_t db, int sc) {
  asm volatile("{\n.reg .pred p;\nsetp.ne.b32 p, %34, 0;\n"
    "wgmma.mma_async.sync.aligned.m64n64k16.f32.bf16.bf16 {%0, %1, %2, %3, %4, %5, %6, %7, %8, %9, %10, %11, %12, %13, %14, %15, %16, %17, %18, %19, %20, %21, %22, %23, %24, %25, %26, %27, %28, %29, %30, %31}, %32, %33, p, 1, 1, %35, %36;\n}\n"
    : "+f"(d[0]), "+f"(d[1]), "+f"(d[2]), "+f"(d[3]), "+f"(d[4]), "+f"(d[5]), "+f"(d[6]), "+f"(d[7]), "+f"(d[8]), "+f"(d[9]), "+f"(d[10]), "+f"(d[11]), "+f"(d[12]), "+f"(d[13]), "+f"(d[14]), "+f"(d[15]), "+f"(d[16]), "+f"(d[17]), "+f"(d[18]), "+f"(d[19]), "+f"(d[20]), "+f"(d[21]), "+f"(d[22]), "+f"(d[23]), "+f"(d[24]), "+f"(d[25]), "+f"(d[26]), "+f"(d[27]), "+f"(d[28]), "+f"(d[29]), "+f"(d[30]), "+f"(d[31])
    : "l"(da), "l"(db), "r"(sc), "n"(TA), "n"(TB));
}
template<int TA, int TB> __device__ __forceinline__ void wgmma_n72(float* d, uint64_t da, uint64_t db, int sc) {
  asm volatile("{\n.reg .pred p;\nsetp.ne.b32 p, %38, 0;\n"
    "wgmma.mma_async.sync.aligned.m64n72k16.f32.bf16.bf16 {%0, %1, %2, %3, %4, %5, %6, %7, %8, %9, %10, %11, %12, %13, %14, %15, %16, %17, %18, %19, %20, %21, %22, %23, %24, %25, %26, %27, %28, %29, %30, %31, %32, %33, %34, %35}, %36, %37, p, 1, 1, %39, %40;\n}\n"
    : "+f"(d[0]), "+f"(d[1]), "+f"(d[2]), "+f"(d[3]), "+f"(d[4]), "+f"(d[5]), "+f"(d[6]), "+f"(d[7]), "+f"(d[8]), "+f"(d[9]), "+f"(d[10]), "+f"(d[11]), "+f"(d[12]), "+f"(d[13]), "+f"(d[14]), "+f"(d[15]), "+f"(d[16]), "+f"(d[17]), "+f"(d[18]), "+f"(d[19]), "+f"(d[20]), "+f"(d[21]), "+f"(d[22]), "+f"(d[23]), "+f"(d[24]), "+f"(d[25]), "+f"(d[26]), "+f"(d[27]), "+f"(d[28]), "+f"(d[29]), "+f"(d[30]), "+f"(d[31]), "+f"(d[32]), "+f"(d[33]), "+f"(d[34]), "+f"(d[35])
    : "l"(da), "l"(db), "r"(sc), "n"(TA), "n"(TB));
}
template<int TA, int TB> __device__ __forceinline__ void wgmma_n80(float* d, uint64_t da, uint64_t db, int sc) {
  asm volatile("{\n.reg .pred p;\nsetp.ne.b32 p, %42, 0;\n"
    "wgmma.mma_async.sync.aligned.m64n80k16.f32.bf16.bf16 {%0, %1, %2, %3, %4, %5, %6, %7, %8, %9, %10, %11, %12, %13, %14, %15, %16, %17, %18, %19, %20, %21, %22, %23, %24, %25, %26, %27, %28, %29, %30, %31, %32, %33, %34, %35, %36, %37, %38, %39}, %40, %41, p, 1, 1, %43, %44;\n}\n"
    : "+f"(d[0]), "+f"(d[1]), "+f"(d[2]), "+f"(d[3]), "+f"(d[4]), "+f"(d[5]), "+f"(d[6]), "+f"(d[7]), "+f"(d[8]), "+f"(d[9]), "+f"(d[10]), "+f"(d[11]), "+f"(d[12]), "+f"(d[13]), "+f"(d[14]), "+f"(d[15]), "+f"(d[16]), "+f"(d[17]), "+f"(d[18]), "+f"(d[19]), "+f"(d[20]), "+f"(d[21]), "+f"(d[22]), "+f"(d[23]), "+f"(d[24]), "+f"(d[25]), "+f"(d[26]), "+f"(d[27]), "+f"(d[28]), "+f"(d[29]), "+f"(d[30]), "+f"(d[31]), "+f"(d[32]), "+f"(d[33]), "+f"(d[34]), "+f"(d[35]), "+f"(d[36]), "+f"(d[37]), "+f"(d[38]), "+f"(d[39])
    : "l"(da), "l"(db), "r"(sc), "n"(TA), "n"(TB));
}
template<int TA, int TB> __device__ __forceinline__ void wgmma_n88(float* d, uint64_t da, uint64_t db, int sc) {
  asm volatile("{\n.reg .pred p;\nsetp.ne.b32 p, %46, 0;\n"
    "wgmma.mma_async.sync.aligned.m64n88k16.f32.bf16.bf16 {%0, %1, %2, %3, %4, %5, %6, %7, %8, %9, %10, %11, %12, %13, %14, %15, %16, %17, %18, %19, %20, %21, %22, %23, %24, %25, %26, %27, %28, %29, %30, %31, %32, %33, %34, %35, %36, %37, %38, %39, %40, %41, %42, %43}, %44, %45, p, 1, 1, %47, %48;\n}\n"
    : "+f"(d[0]), "+f"(d[1]), "+f"(d[2]), "+f"(d[3]), "+f"(d[4]), "+f"(d[5]), "+f"(d[6]), "+f"(d[7]), "+f"(d[8]), "+f"(d[9]), "+f"(d[10]), "+f"(d[11]), "+f"(d[12]), "+f"(d[13]), "+f"(d[14]), "+f"(d[15]), "+f"(d[16]), "+f"(d[17]), "+f"(d[18]), "+f"(d[19]), "+f"(d[20]), "+f"(d[21]), "+f"(d[22]), "+f"(d[23]), "+f"(d[24]), "+f"(d[25]), "+f"(d[26]), "+f"(d[27]), "+f"(d[28]), "+f"(d[29]), "+f"(d[30]), "+f"(d[31]), "+f"(d[32]), "+f"(d[33]), "+f"(d[34]), "+f"(d[35]), "+f"(d[36]), "+f"(d[37]), "+f"(d[38]), "+f"(d[39]), "+f"(d[40]), "+f"(d[41]), "+f"(d[42]), "+f"(d[43])
    : "l"(da), "l"(db), "r"(sc), "n"(TA), "n"(TB));
}
template<int TA, int TB> __device__ __forceinline__ void wgmma_n96(float* d, uint64_t da, uint64_t db, int sc) {
  asm volatile("{\n.reg .pred p;\nsetp.ne.b32 p, %50, 0;\n"
    "wgmma.mma_async.sync.aligned.m64n96k16.f32.bf16.bf16 {%0, %1, %2, %3, %4, %5, %6, %7, %8, %9, %10, %11, %12, %13, %14, %15, %16, %17, %18, %19, %20, %21, %22, %23, %24, %25, %26, %27, %28, %29, %30, %31, %32, %33, %34, %35, %36, %37, %38, %39, %40, %41, %42, %43, %44, %45, %46, %47}, %48, %49, p, 1, 1, %51, %52;\n}\n"
    : "+f"(d[0]), "+f"(d[1]), "+f"(d[2]), "+f"(d[3]), "+f"(d[4]), "+f"(d[5]), "+f"(d[6]), "+f"(d[7]), "+f"(d[8]), "+f"(d[9]), "+f"(d[10]), "+f"(d[11]), "+f"(d[12]), "+f"(d[13]), "+f"(d[14]), "+f"(d[15]), "+f"(d[16]), "+f"(d[17]), "+f"(d[18]), "+f"(d[19]), "+f"(d[20]), "+f"(d[21]), "+f"(d[22]), "+f"(d[23]), "+f"(d[24]), "+f"(d[25]), "+f"(d[26]), "+f"(d[27]), "+f"(d[28]), "+f"(d[29]), "+f"(d[30]), "+f"(d[31]), "+f"(d[32]), "+f"(d[33]), "+f"(d[34]), "+f"(d[35]), "+f"(d[36]), "+f"(d[37]), "+f"(d[38]), "+f"(d[39]), "+f"(d[40]), "+f"(d[41]), "+f"(d[42]), "+f"(d[43]), "+f"(d[44]), "+f"(d[45]), "+f"(d[46]), "+f"(d[47])
    : "l"(da), "l"(db), "r"(sc), "n"(TA), "n"(TB));
}
template<int TA, int TB> __device__ __forceinline__ void wgmma_n104(float* d, uint64_t da, uint64_t db, int sc) {
  asm volatile("{\n.reg .pred p;\nsetp.ne.b32 p, %54, 0;\n"
    "wgmma.mma_async.sync.aligned.m64n104k16.f32.bf16.bf16 {%0, %1, %2, %3, %4, %5, %6, %7, %8, %9, %10, %11, %12, %13, %14, %15, %16, %17, %18, %19, %20, %21, %22, %23, %24, %25, %26, %27, %28, %29, %30, %31, %32, %33, %34, %35, %36, %37, %38, %39, %40, %41, %42, %43, %44, %45, %46, %47, %48, %49, %50, %51}, %52, %53, p, 1, 1, %55, %56;\n}\n"
    : "+f"(d[0]), "+f"(d[1]), "+f"(d[2]), "+f"(d[3]), "+f"(d[4]), "+f"(d[5]), "+f"(d[6]), "+f"(d[7]), "+f"(d[8]), "+f"(d[9]), "+f"(d[10]), "+f"(d[11]), "+f"(d[12]), "+f"(d[13]), "+f"(d[14]), "+f"(d[15]), "+f"(d[16]), "+f"(d[17]), "+f"(d[18]), "+f"(d[19]), "+f"(d[20]), "+f"(d[21]), "+f"(d[22]), "+f"(d[23]), "+f"(d[24]), "+f"(d[25]), "+f"(d[26]), "+f"(d[27]), "+f"(d[28]), "+f"(d[29]), "+f"(d[30]), "+f"(d[31]), "+f"(d[32]), "+f"(d[33]), "+f"(d[34]), "+f"(d[35]), "+f"(d[36]), "+f"(d[37]), "+f"(d[38]), "+f"(d[39]), "+f"(d[40]), "+f"(d[41]), "+f"(d[42]), "+f"(d[43]), "+f"(d[44]), "+f"(d[45]), "+f"(d[46]), "+f"(d[47]), "+f"(d[48]), "+f"(d[49]), "+f"(d[50]), "+f"(d[51])
    : "l"(da), "l"(db), "r"(sc), "n"(TA), "n"(TB));
}
template<int TA, int TB> __device__ __forceinline__ void wgmma_n112(float* d, uint64_t da, uint64_t db, int sc) {
  asm volatile("{\n.reg .pred p;\nsetp.ne.b32 p, %58, 0;\n"
    "wgmma.mma_async.sync.aligned.m64n112k16.f32.bf16.bf16 {%0, %1, %2, %3, %4, %5, %6, %7, %8, %9, %10, %11, %12, %13, %14, %15, %16, %17, %18, %19, %20, %21, %22, %23, %24, %25, %26, %27, %28, %29, %30, %31, %32, %33, %34, %35, %36, %37, %38, %39, %40, %41, %42, %43, %44, %45, %46, %47, %48, %49, %50, %51, %52, %53, %54, %55}, %56, %57, p, 1, 1, %59, %60;\n}\n"
    : "+f"(d[0]), "+f"(d[1]), "+f"(d[2]), "+f"(d[3]), "+f"(d[4]), "+f"(d[5]), "+f"(d[6]), "+f"(d[7]), "+f"(d[8]), "+f"(d[9]), "+f"(d[10]), "+f"(d[11]), "+f"(d[12]), "+f"(d[13]), "+f"(d[14]), "+f"(d[15]), "+f"(d[16]), "+f"(d[17]), "+f"(d[18]), "+f"(d[19]), "+f"(d[20]), "+f"(d[21]), "+f"(d[22]), "+f"(d[23]), "+f"(d[24]), "+f"(d[25]), "+f"(d[26]), "+f"(d[27]), "+f"(d[28]), "+f"(d[29]), "+f"(d[30]), "+f"(d[31]), "+f"(d[32]), "+f"(d[33]), "+f"(d[34]), "+f"(d[35]), "+f"(d[36]), "+f"(d[37]), "+f"(d[38]), "+f"(d[39]), "+f"(d[40]), "+f"(d[41]), "+f"(d[42]), "+f"(d[43]), "+f"(d[44]), "+f"(d[45]), "+f"(d[46]), "+f"(d[47]), "+f"(d[48]), "+f"(d[49]), "+f"(d[50]), "+f"(d[51]), "+f"(d[52]), "+f"(d[53]), "+f"(d[54]), "+f"(d[55])
    : "l"(da), "l"(db), "r"(sc), "n"(TA), "n"(TB));
}
template<int TA, int TB> __device__ __forceinline__ void wgmma_n120(float* d, uint64_t da, uint64_t db, int sc) {
  asm volatile("{\n.reg .pred p;\nsetp.ne.b32 p, %62, 0;\n"
    "wgmma.mma_async.sync.aligned.m64n120k16.f32.bf16.bf16 {%0, %1, %2, %3, %4, %5, %6, %7, %8, %9, %10, %11, %12, %13, %14, %15, %16, %17, %18, %19, %20, %21, %22, %23, %24, %25, %26, %27, %28, %29, %30, %31, %32, %33, %34, %35, %36, %37, %38, %39, %40, %41, %42, %43, %44, %45, %46, %47, %48, %49, %50, %51, %52, %53, %54, %55, %56, %57, %58, %59}, %60, %61, p, 1, 1, %63, %64;\n}\n"
    : "+f"(d[0]), "+f"(d[1]), "+f"(d[2]), "+f"(d[3]), "+f"(d[4]), "+f"(d[5]), "+f"(d[6]), "+f"(d[7]), "+f"(d[8]), "+f"(d[9]), "+f"(d[10]), "+f"(d[11]), "+f"(d[12]), "+f"(d[13]), "+f"(d[14]), "+f"(d[15]), "+f"(d[16]), "+f"(d[17]), "+f"(d[18]), "+f"(d[19]), "+f"(d[20]), "+f"(d[21]), "+f"(d[22]), "+f"(d[23]), "+f"(d[24]), "+f"(d[25]), "+f"(d[26]), "+f"(d[27]), "+f"(d[28]), "+f"(d[29]), "+f"(d[30]), "+f"(d[31]), "+f"(d[32]), "+f"(d[33]), "+f"(d[34]), "+f"(d[35]), "+f"(d[36]), "+f"(d[37]), "+f"(d[38]), "+f"(d[39]), "+f"(d[40]), "+f"(d[41]), "+f"(d[42]), "+f"(d[43]), "+f"(d[44]), "+f"(d[45]), "+f"(d[46]), "+f"(d[47]), "+f"(d[48]), "+f"(d[49]), "+f"(d[50]), "+f"(d[51]), "+f"(d[52]), "+f"(d[53]), "+f"(d[54]), "+f"(d[55]), "+f"(d[56]), "+f"(d[57]), "+f"(d[58]), "+f"(d[59])
    : "l"(da), "l"(db), "r"(sc), "n"(TA), "n"(TB));
}
template<int TA, int TB> __device__ __forceinline__ void wgmma_n128(float* d, uint64_t da, uint64_t db, int sc) {
  asm volatile("{\n.reg .pred p;\nsetp.ne.b32 p, %66, 0;\n"
    "wgmma.mma_async.sync.aligned.m64n128k16.f32.bf16.bf16 {%0, %1, %2, %3, %4, %5, %6, %7, %8, %9, %10, %11, %12, %13, %14, %15, %16, %17, %18, %19, %20, %21, %22, %23, %24, %25, %26, %27, %28, %29, %30, %31, %32, %33, %34, %35, %36, %37, %38, %39, %40, %41, %42, %43, %44, %45, %46, %47, %48, %49, %50, %51, %52, %53, %54, %55, %56, %57, %58, %59, %60, %61, %62, %63}, %64, %65, p, 1, 1, %67, %68;\n}\n"
    : "+f"(d[0]), "+f"(d[1]), "+f"(d[2]), "+f"(d[3]), "+f"(d[4]), "+f"(d[5]), "+f"(d[6]), "+f"(d[7]), "+f"(d[8]), "+f"(d[9]), "+f"(d[10]), "+f"(d[11]), "+f"(d[12]), "+f"(d[13]), "+f"(d[14]), "+f"(d[15]), "+f"(d[16]), "+f"(d[17]), "+f"(d[18]), "+f"(d[19]), "+f"(d[20]), "+f"(d[21]), "+f"(d[22]), "+f"(d[23]), "+f"(d[24]), "+f"(d[25]), "+f"(d[26]), "+f"(d[27]), "+f"(d[28]), "+f"(d[29]), "+f"(d[30]), "+f"(d[31]), "+f"(d[32]), "+f"(d[33]), "+f"(d[34]), "+f"(d[35]), "+f"(d[36]), "+f"(d[37]), "+f"(d[38]), "+f"(d[39]), "+f"(d[40]), "+f"(d[41]), "+f"(d[42]), "+f"(d[43]), "+f"(d[44]), "+f"(d[45]), "+f"(d[46]), "+f"(d[47]), "+f"(d[48]), "+f"(d[49]), "+f"(d[50]), "+f"(d[51]), "+f"(d[52]), "+f"(d[53]), "+f"(d[54]), "+f"(d[55]), "+f"(d[56]), "+f"(d[57]), "+f"(d[58]), "+f"(d[59]), "+f"(d[60]), "+f"(d[61]), "+f"(d[62]), "+f"(d[63])
    : "l"(da), "l"(db), "r"(sc), "n"(TA), "n"(TB));
}
template<int TA, int TB> __device__ __forceinline__ void wgmma_n160(float* d, uint64_t da, uint64_t db, int sc) {
  asm volatile("{\n.reg .pred p;\nsetp.ne.b32 p, %82, 0;\n"
    "wgmma.mma_async.sync.aligned.m64n160k16.f32.bf16.bf16 {%0, %1, %2, %3, %4, %5, %6, %7, %8, %9, %10, %11, %12, %13, %14, %15, %16, %17, %18, %19, %20, %21, %22, %23, %24, %25, %26, %27, %28, %29, %30, %31, %32, %33, %34, %35, %36, %37, %38, %39, %40, %41, %42, %43, %44, %45, %46, %47, %48, %49, %50, %51, %52, %53, %54, %55, %56, %57, %58, %59, %60, %61, %62, %63, %64, %65, %66, %67, %68, %69, %70, %71, %72, %73, %74, %75, %76, %77, %78, %79}, %80, %81, p, 1, 1, %83, %84;\n}\n"
    : "+f"(d[0]), "+f"(d[1]), "+f"(d[2]), "+f"(d[3]), "+f"(d[4]), "+f"(d[5]), "+f"(d[6]), "+f"(d[7]), "+f"(d[8]), "+f"(d[9]), "+f"(d[10]), "+f"(d[11]), "+f"(d[12]), "+f"(d[13]), "+f"(d[14]), "+f"(d[15]), "+f"(d[16]), "+f"(d[17]), "+f"(d[18]), "+f"(d[19]), "+f"(d[20]), "+f"(d[21]), "+f"(d[22]), "+f"(d[23]), "+f"(d[24]), "+f"(d[25]), "+f"(d[26]), "+f"(d[27]), "+f"(d[28]), "+f"(d[29]), "+f"(d[30]), "+f"(d[31]), "+f"(d[32]), "+f"(d[33]), "+f"(d[34]), "+f"(d[35]), "+f"(d[36]), "+f"(d[37]), "+f"(d[38]), "+f"(d[39]), "+f"(d[40]), "+f"(d[41]), "+f"(d[42]), "+f"(d[43]), "+f"(d[44]), "+f"(d[45]), "+f"(d[46]), "+f"(d[47]), "+f"(d[48]), "+f"(d[49]), "+f"(d[50]), "+f"(d[51]), "+f"(d[52]), "+f"(d[53]), "+f"(d[54]), "+f"(d[55]), "+f"(d[56]), "+f"(d[57]), "+f"(d[58]), "+f"(d[59]), "+f"(d[60]), "+f"(d[61]), "+f"(d[62]), "+f"(d[63]), "+f"(d[64]), "+f"(d[65]), "+f"(d[66]), "+f"(d[67]), "+f"(d[68]), "+f"(d[69]), "+f"(d[70]), "+f"(d[71]), "+f"(d[72]), "+f"(d[73]), "+f"(d[74]), "+f"(d[75]), "+f"(d[76]), "+f"(d[77]), "+f"(d[78]), "+f"(d[79])
    : "l"(da), "l"(db), "r"(sc), "n"(TA), "n"(TB));
}
template<int TA, int TB> __device__ __forceinline__ void wgmma_n192(float* d, uint64_t da, uint64_t db, int sc) {
  asm volatile("{\n.reg .pred p;\nsetp.ne.b32 p, %98, 0;\n"
    "wgmma.mma_async.sync.aligned.m64n192k16.f32.bf16.bf16 {%0, %1, %2, %3, %4, %5, %6, %7, %8, %9, %10, %11, %12, %13, %14, %15, %16, %17, %18, %19, %20, %21, %22, %23, %24, %25, %26, %27, %28, %29, %30, %31, %32, %33, %34, %35, %36, %37, %38, %39, %40, %41, %42, %43, %44, %45, %46, %47, %48, %49, %50, %51, %52, %53, %54, %55, %56, %57, %58, %59, %60, %61, %62, %63, %64, %65, %66, %67, %68, %69, %70, %71, %72, %73, %74, %75, %76, %77, %78, %79, %80, %81, %82, %83, %84, %85, %86, %87, %88, %89, %90, %91, %92, %93, %94, %95}, %96, %97, p, 1, 1, %99, %100;\n}\n"
    : "+f"(d[0]), "+f"(d[1]), "+f"(d[2]), "+f"(d[3]), "+f"(d[4]), "+f"(d[5]), "+f"(d[6]), "+f"(d[7]), "+f"(d[8]), "+f"(d[9]), "+f"(d[10]), "+f"(d[11]), "+f"(d[12]), "+f"(d[13]), "+f"(d[14]), "+f"(d[15]), "+f"(d[16]), "+f"(d[17]), "+f"(d[18]), "+f"(d[19]), "+f"(d[20]), "+f"(d[21]), "+f"(d[22]), "+f"(d[23]), "+f"(d[24]), "+f"(d[25]), "+f"(d[26]), "+f"(d[27]), "+f"(d[28]), "+f"(d[29]), "+f"(d[30]), "+f"(d[31]), "+f"(d[32]), "+f"(d[33]), "+f"(d[34]), "+f"(d[35]), "+f"(d[36]), "+f"(d[37]), "+f"(d[38]), "+f"(d[39]), "+f"(d[40]), "+f"(d[41]), "+f"(d[42]), "+f"(d[43]), "+f"(d[44]), "+f"(d[45]), "+f"(d[46]), "+f"(d[47]), "+f"(d[48]), "+f"(d[49]), "+f"(d[50]), "+f"(d[51]), "+f"(d[52]), "+f"(d[53]), "+f"(d[54]), "+f"(d[55]), "+f"(d[56]), "+f"(d[57]), "+f"(d[58]), "+f"(d[59]), "+f"(d[60]), "+f"(d[61]), "+f"(d[62]), "+f"(d[63]), "+f"(d[64]), "+f"(d[65]), "+f"(d[66]), "+f"(d[67]), "+f"(d[68]), "+f"(d[69]), "+f"(d[70]), "+f"(d[71]), "+f"(d[72]), "+f"(d[73]), "+f"(d[74]), "+f"(d[75]), "+f"(d[76]), "+f"(d[77]), "+f"(d[78]), "+f"(d[79]), "+f"(d[80]), "+f"(d[81]), "+f"(d[82]), "+f"(d[83]), "+f"(d[84]), "+f"(d[85]), "+f"(d[86]), "+f"(d[87]), "+f"(d[88]), "+f"(d[89]), "+f"(d[90]), "+f"(d[91]), "+f"(d[92]), "+f"(d[93]), "+f"(d[94]), "+f"(d[95])
    : "l"(da), "l"(db), "r"(sc), "n"(TA), "n"(TB));
}
template<int N, int TA, int TB> __device__ __forceinline__ void wgmma_ss(float* d, uint64_t da, uint64_t db, int sc) {
  if constexpr (N == 8) wgmma_n8<TA,TB>(d, da, db, sc);
  if constexpr (N == 16) wgmma_n16<TA,TB>(d, da, db, sc);
  if constexpr (N == 24) wgmma_n24<TA,TB>(d, da, db, sc);
  if constexpr (N == 32) wgmma_n32<TA,TB>(d, da, db, sc);
  if constexpr (N == 40) wgmma_n40<TA,TB>(d, da, db, sc);
  if constexpr (N == 48) wgmma_n48<TA,TB>(d, da, db, sc);
  if constexpr (N == 56) wgmma_n56<TA,TB>(d, da, db, sc);
  if constexpr (N == 64) wgmma_n64<TA,TB>(d, da, db, sc);
  if constexpr (N == 72) wgmma_n72<TA,TB>(d, da, db, sc);
  if constexpr (N == 80) wgmma_n80<TA,TB>(d, da, db, sc);
  if constexpr (N == 88) wgmma_n88<TA,TB>(d, da, db, sc);
  if constexpr (N == 96) wgmma_n96<TA,TB>(d, da, db, sc);
  if constexpr (N == 104) wgmma_n104<TA,TB>(d, da, db, sc);
  if constexpr (N == 112) wgmma_n112<TA,TB>(d, da, db, sc);
  if constexpr (N == 120) wgmma_n120<TA,TB>(d, da, db, sc);
  if constexpr (N == 128) wgmma_n128<TA,TB>(d, da, db, sc);
  if constexpr (N == 160) wgmma_n160<TA,TB>(d, da, db, sc);
  if constexpr (N == 192) wgmma_n192<TA,TB>(d, da, db, sc);
}

constexpr int NGRP = 260;
constexpr uint32_t G1_STAGE = 57344;
constexpr uint32_t OFF_U = 131072;
constexpr uint32_t OFF_H = 172032;
constexpr uint32_t H_PITCH = 4352;
constexpr uint32_t OFF_ZS = 215552;
constexpr uint32_t OFF_EX = OFF_ZS + 12544;
constexpr uint32_t OFF_G = OFF_EX + 2304;
constexpr uint32_t OFF_BAR = OFF_G + 640;
constexpr uint32_t OFF_GS = OFF_BAR + 448;
constexpr uint32_t SMEM_BYTES = OFF_GS + 64 + 512;
constexpr uint32_t OFF_V = OFF_H + 23040;
constexpr uint32_t OFF_US = OFF_ZS + 1536;
constexpr int NCTA = 130;
constexpr uint32_t SB0 = 1024;

enum { B_FULL1 = 0, B_KV = 3,
       B_FULL2 = 4, B_EMPTY2 = 9, B_CD = 14, B_HLD = 19, B_QG = 20, B_GATE = 21, B_GS = 22,
       B_HDR = 23, B_XCH = 24, B_Z = 26, B_XF = 27,
       B_EMPTY1 = 28, B_G1DONE = 31, B_Z3 = 32, B_ZF = 33,
       B_R2FREE = 34, B_UFULL = 35,
       B_SIGH = 40, B_SIGZ = 44, B_QC = 49, B_COUNT = 52 };
enum { C_H = 0, C_U = 16, C_Z = 24, C_DONE = 34, C_COUNT = 35 };
__host__ __device__ constexpr uint32_t slotF(int s) { return s == 0 ? 114688 : s == 1 ? 32768 : s == 2 ? 90112 : s == 3 ? 49152 : 139264; }
__host__ __device__ constexpr uint32_t slotO(int s) { return s == 3 ? 106496 : slotF(s) + 8192; }
__host__ __device__ constexpr uint32_t slotB0(int s) { return s == 0 ? 0 : s == 1 ? 20480 : s == 2 ? 67584 : s == 3 ? 155648 : 176128; }
__host__ __device__ constexpr uint32_t slotB1(int s) { return s == 1 ? 57344 : slotB0(s) + 10240; }
constexpr uint32_t OFF_Q = 196608, OFF_XCH = OFF_Q, OFF_Z = slotB0(2), OFF_OUT = slotB0(3);
__device__ __forceinline__ uint32_t zstage(int ch) { return ch < 3 ? OFF_ZS + ch * 4160 : OFF_U + (4 - ch) * 8192; }

__device__ __align__(1024) __nv_bfloat16 g_Hs[48 * NGRP * 256];
__device__ __align__(1024) __nv_bfloat16 g_U[640 * 2 * 2048];
__device__ __align__(1024) __nv_bfloat16 g_zT[640 * NGRP * 8];
__device__ __align__(1024) float g_gate[NGRP * 8];
__device__ __align__(1024) unsigned g_cnt[C_COUNT * 32];
#define TS(i) do { } while (0)
#define TSB(i) do { } while (0)

__device__ __forceinline__ uint32_t smem_u32(const void* p) { return (uint32_t)__cvta_generic_to_shared(p); }
__device__ __forceinline__ int fresh_lane() {
  int r;
  asm volatile("mov.u32 %0, %%laneid;" : "=r"(r));
  return r;
}
__device__ __forceinline__ uint64_t mkdesc(uint32_t addr, uint32_t lbo, uint32_t sbo, uint32_t swz) {
  return (uint64_t)((addr & 0x3FFFF) >> 4) | ((uint64_t)(lbo >> 4) << 16) | ((uint64_t)(sbo >> 4) << 32) | ((uint64_t)swz << 62);
}
__device__ __forceinline__ void wg_fence() { asm volatile("wgmma.fence.sync.aligned;" ::: "memory"); }
__device__ __forceinline__ void wg_commit() { asm volatile("wgmma.commit_group.sync.aligned;" ::: "memory"); }
template <int N> __device__ __forceinline__ void wg_wait() { asm volatile("wgmma.wait_group.sync.aligned %0;" ::"n"(N) : "memory"); }
template <int N> __device__ __forceinline__ void pin(float* d) {
#pragma unroll
  for (int i = 0; i < N; i++) asm volatile("" : "+f"(d[i])::"memory");
}
__device__ __forceinline__ void mbar_init(uint32_t a, int c) { asm volatile("mbarrier.init.shared::cta.b64 [%0], %1;" ::"r"(a), "r"(c) : "memory"); }
__device__ __forceinline__ void mbar_expect(uint32_t a, uint32_t b) { asm volatile("mbarrier.arrive.expect_tx.shared::cta.b64 _, [%0], %1;" ::"r"(a), "r"(b) : "memory"); }
__device__ __forceinline__ uint32_t peer_addr(uint32_t a) {
  uint32_t r;
  asm("mapa.shared::cluster.u32 %0, %1, %2;" : "=r"(r) : "r"(a), "r"((blockIdx.x & 1) ^ 1));
  return r;
}
__device__ __forceinline__ void mbar_arrive(uint32_t a) { asm volatile("mbarrier.arrive.shared::cta.b64 _, [%0];" ::"r"(a) : "memory"); }
__device__ __forceinline__ bool elect_one() {
  uint32_t e;
  asm volatile("{\n.reg .pred p;\nelect.sync _|p, 0xffffffff;\nselp.u32 %0,1,0,p;\n}" : "=r"(e));
  return e;
}
__device__ __forceinline__ void mbar_wait_t(uint32_t a, uint32_t ph) {
  asm volatile(
      "{\n.reg .pred p, q;\n.reg .u32 n;\n"
      "mbarrier.try_wait.parity.shared::cta.b64 p, [%0], %1;\n"
      "@p bra DONE_%=;\n"
      "mov.u32 n, 0;\n"
      "WAIT_%=:\n"
      "mbarrier.try_wait.parity.shared::cta.b64 p, [%0], %1;\n"
      "@p bra DONE_%=;\n"
      "add.u32 n, n, 1;\n"
      "setp.lt.u32 q, n, 0x40000;\n"
      "@q bra WAIT_%=;\n"
      "trap;\n"
      "DONE_%=:\n}" ::"r"(a), "r"(ph) : "memory");
}
__device__ __forceinline__ void mbar_wait(uint32_t a, uint32_t ph) {
  asm volatile(
      "{\n.reg .pred p, q;\n.reg .u32 n;\nmov.u32 n, 0;\n"
      "WAIT_%=:\n"
      "mbarrier.try_wait.parity.shared::cta.b64 p, [%0], %1;\n"
      "@p bra DONE_%=;\n"
      "add.u32 n, n, 1;\n"
      "setp.lt.u32 q, n, 0x80000;\n"
      "@q bra WAIT_%=;\n"
      "DONE_%=:\n}" ::"r"(a), "r"(ph) : "memory");
}
__device__ __forceinline__ void flag_wait(const unsigned* p0, const unsigned* p1, unsigned target) {
  int it = 0;
  while (true) {
    unsigned v0, v1;
    asm volatile("ld.relaxed.gpu.global.u32 %0, [%1];" : "=r"(v0) : "l"(p0) : "memory");
    asm volatile("ld.relaxed.gpu.global.u32 %0, [%1];" : "=r"(v1) : "l"(p1) : "memory");
    if (min(v0, v1) >= target) break;
    if (++it > (1 << 21)) __trap();
  }
  asm volatile("fence.proxy.async.global;" ::: "memory");
}
__device__ __forceinline__ void flag_add(unsigned* p) {
  asm volatile("red.relaxed.gpu.global.add.u32 [%0], 1;" ::"l"(p) : "memory");
}
__device__ __forceinline__ void bar_sync(int id, int n) { asm volatile("bar.sync %0, %1;" ::"r"(id), "r"(n) : "memory"); }
__device__ __forceinline__ void bar_arrive(int id, int n) { asm volatile("bar.arrive %0, %1;" ::"r"(id), "r"(n) : "memory"); }
__device__ __forceinline__ void bulk_g2s(uint32_t dst, const void* src, uint32_t bytes, uint32_t bar) {
  asm volatile("cp.async.bulk.shared::cluster.global.mbarrier::complete_tx::bytes [%0], [%1], %2, [%3];" ::"r"(dst), "l"(src), "r"(bytes), "r"(bar) : "memory");
}
__device__ __forceinline__ void bulk_s2g(void* dst, uint32_t src, uint32_t bytes) {
  asm volatile("cp.async.bulk.global.shared::cta.bulk_group [%0], [%1], %2;" ::"l"(dst), "r"(src), "r"(bytes) : "memory");
}
__device__ __forceinline__ void bulk_prefetch(const void* src, uint32_t bytes) {
  asm volatile("cp.async.bulk.prefetch.L2.global [%0], %1;" ::"l"(src), "r"(bytes) : "memory");
}
__device__ __forceinline__ void tma2(uint32_t dst, const CUtensorMap* m, int c0, int c1, uint32_t bar) {
  asm volatile("cp.async.bulk.tensor.2d.shared::cluster.global.mbarrier::complete_tx::bytes [%0], [%1, {%3,%4}], [%2];" ::"r"(dst), "l"(m), "r"(bar), "r"(c0), "r"(c1) : "memory");
}
__device__ __forceinline__ void tma3(uint32_t dst, const CUtensorMap* m, int c0, int c1, int c2, uint32_t bar) {
  asm volatile("cp.async.bulk.tensor.3d.shared::cluster.global.mbarrier::complete_tx::bytes [%0], [%1, {%3,%4,%5}], [%2];" ::"r"(dst), "l"(m), "r"(bar), "r"(c0), "r"(c1), "r"(c2) : "memory");
}
__device__ __forceinline__ void tma4(uint32_t dst, const CUtensorMap* m, int c0, int c1, int c2, int c3, uint32_t bar) {
  asm volatile("cp.async.bulk.tensor.4d.shared::cluster.global.mbarrier::complete_tx::bytes [%0], [%1, {%3,%4,%5,%6}], [%2];" ::"r"(dst), "l"(m), "r"(bar), "r"(c0), "r"(c1), "r"(c2), "r"(c3) : "memory");
}
__device__ __forceinline__ void prefetch_map(const CUtensorMap* m) { asm volatile("prefetch.tensormap [%0];" ::"l"(m) : "memory"); }
__device__ __forceinline__ void tma2_store(const CUtensorMap* m, uint32_t src, int c0, int c1) {
  asm volatile("cp.async.bulk.tensor.2d.global.shared::cta.bulk_group [%0, {%2,%3}], [%1];" ::"l"(m), "r"(src), "r"(c0), "r"(c1) : "memory");
}
__device__ __forceinline__ void tma3_store(const CUtensorMap* m, uint32_t src, int c0, int c1, int c2) {
  asm volatile("cp.async.bulk.tensor.3d.global.shared::cta.bulk_group [%0, {%2,%3,%4}], [%1];" ::"l"(m), "r"(src), "r"(c0), "r"(c1), "r"(c2) : "memory");
}
__device__ __forceinline__ void tma4_store(const CUtensorMap* m, uint32_t src, int c0, int c1, int c2, int c3) {
  asm volatile("cp.async.bulk.tensor.4d.global.shared::cta.bulk_group [%0, {%2,%3,%4,%5}], [%1];" ::"l"(m), "r"(src), "r"(c0), "r"(c1), "r"(c2), "r"(c3) : "memory");
}
__device__ __forceinline__ uint32_t pack_bf16(float lo, float hi) {
  uint32_t r;
  asm("cvt.rn.bf16x2.f32 %0, %1, %2;" : "=r"(r) : "f"(hi), "f"(lo));
  return r;
}
__device__ __forceinline__ float tanh_fast(float x) {
  float r;
  asm("tanh.approx.f32 %0, %1;" : "=f"(r) : "f"(x));
  return r;
}
__device__ __forceinline__ uint32_t bmul2(uint32_t a, uint32_t b) {
  uint32_t r;
  asm("mul.rn.bf16x2 %0, %1, %2;" : "=r"(r) : "r"(a), "r"(b));
  return r;
}
__device__ __forceinline__ uint32_t bfma2(uint32_t a, uint32_t b, uint32_t c) {
  uint32_t r;
  asm("fma.rn.bf16x2 %0, %1, %2, %3;" : "=r"(r) : "r"(a), "r"(b), "r"(c));
  return r;
}
__device__ __forceinline__ uint2 lds64(uint32_t a) {
  uint2 r;
  asm volatile("ld.volatile.shared.v2.u32 {%0,%1}, [%2];" : "=r"(r.x), "=r"(r.y) : "r"(a) : "memory");
  return r;
}
__device__ __forceinline__ float bflo(uint32_t v) { return __uint_as_float(v << 16); }
__device__ __forceinline__ float bfhi(uint32_t v) { return __uint_as_float(v & 0xffff0000u); }

__device__ __forceinline__ uint32_t badd2(uint32_t a, uint32_t b) {
  uint32_t r;
  asm("add.rn.bf16x2 %0, %1, %2;" : "=r"(r) : "r"(a), "r"(b));
  return r;
}
template <int I0, int I1> __device__ __forceinline__ void conv_mma(float* d, uint64_t da, uint64_t db) {
  if constexpr (I0 < I1) {
    constexpr int S = I0 >> 1, PH = I0 & 1;
    wgmma_ss<128 - 8 * S, 1, 1>(d, da + (PH * (H_PITCH >> 4) + 16 * S), db + (PH * 256 + 16 * S), I0 != 0);
    conv_mma<I0 + 1, I1>(d, da, db);
  }
}
__device__ __forceinline__ uint64_t conv_da(int ch) { return mkdesc(SB0 + OFF_H + ch * 2 * H_PITCH, 128, 32, 0); }
__device__ __forceinline__ uint64_t conv_db(int ch) { return mkdesc(SB0 + OFF_U + (4 - ch) * 8192, 128, 256, 0); }
__device__ __forceinline__ void sts128_if(bool p, uint32_t a, const uint32_t* v) {
  asm volatile("{\n.reg .pred p;\nsetp.ne.u32 p, %5, 0;\n@p st.shared.v4.u32 [%0], {%1,%2,%3,%4};\n}" ::"r"(a), "r"(v[0]), "r"(v[1]), "r"(v[2]), "r"(v[3]), "r"((uint32_t)p) : "memory");
}
__device__ __forceinline__ void lds128_if(bool p, uint32_t a, uint32_t* v) {
  asm volatile("{\n.reg .pred p;\nsetp.ne.u32 p, %5, 0;\n@p ld.shared.v4.u32 {%0,%1,%2,%3}, [%4];\n}" : "+r"(v[0]), "+r"(v[1]), "+r"(v[2]), "+r"(v[3]) : "r"(a), "r"((uint32_t)p) : "memory");
}
__host__ __device__ constexpr int cvs(int next, int i) {
  constexpr int a[8] = {0, 2, 4, 6, 8, 11, 13, 15}, b[8] = {CV4};
  return CV0 + (next == 1 ? a[i] : b[i]) > 32 ? 32 : CV0 + (next == 1 ? a[i] : b[i]);
}
template <int NEXT>
__device__ __forceinline__ void conv_finish(const float* d, uint32_t sb, uint32_t bar, int ch, int wg, int w, float* dn, uint64_t da, uint64_t db) {
  const int lane = fresh_lane();
  const int g = lane >> 2, q = lane & 3;
  const int c = q & 1, mu = 8 * (q >> 1) + g;
  const int mu1 = (mu + 15) & 15, mu2 = (mu + (c ? 2 : 14)) & 15;
  const int src1 = 4 * (mu1 & 7) + 2 * (mu1 >> 3) + c;
  const int src2 = 4 * (mu2 & 7) + 2 * (mu2 >> 3) + (c ^ 1);
  const bool last = mu == 15, pA = (c == 0) || (mu >= 14);
  const bool impX = lane < 2, impY = (c == 1) && (mu >= 14);
  const int oo = 32 * w + (c ? mu2 : 16 + mu);
  const uint32_t zs = sb + zstage(ch);
  const uint32_t ex = sb + OFF_EX + (ch & 3) * 128 + (impX ? lane : 2 + (mu & 1)) * 32;
  uint32_t p0[8], xr[8], s1[8], e[8];
#pragma unroll
  for (int k = 0; k < 8; k++) {
    const int i = 60 - 8 * k;
    const uint32_t p1 = pack_bf16(d[i + 1], d[i - 3]), p3 = pack_bf16(d[i + 3], d[i - 1]);
    s1[k] = badd2(pack_bf16(d[i + 2], d[i - 2]), __shfl_sync(0xffffffffu, last ? p1 : p3, src1));
    xr[k] = __shfl_sync(0xffffffffu, last ? p3 : p1, src1);
    p0[k] = pack_bf16(d[i], d[i - 4]);
    if (NEXT && k == 1) conv_mma<cvs(NEXT, 0), cvs(NEXT, 1)>(dn, da, db);
    if (NEXT && k == 3) conv_mma<cvs(NEXT, 1), cvs(NEXT, 2)>(dn, da, db);
    if (NEXT && k == 5) conv_mma<cvs(NEXT, 2), cvs(NEXT, 3)>(dn, da, db);
    if (NEXT && k == 7) conv_mma<cvs(NEXT, 3), cvs(NEXT, 4)>(dn, da, db);
  }
  const uint32_t sh = w == 3 ? 0x5432 : 0x7654;
#pragma unroll
  for (int k = 0; k < 8; k++) e[k] = impX ? xr[k] : s1[k];
#pragma unroll
  for (int k = 7; k >= 0; k--) e[k] = __byte_perm(k ? e[k - 1] : 0u, e[k], sh);
  sts128_if(impX || impY, ex + ((w + 1) & 3) * 512, e);
  sts128_if(impX || impY, ex + ((w + 1) & 3) * 512 + 16, e + 4);
  if (NEXT) conv_mma<cvs(NEXT, 4), cvs(NEXT, 5)>(dn, da, db);
  bar_sync(3 + wg, 128);
  if (w == 0 && lane == 0) mbar_arrive(bar + 8 * (B_CD + ch));
  lds128_if(impX, ex + w * 512, xr);
  lds128_if(impX, ex + w * 512 + 16, xr + 4);
  lds128_if(impY, ex + w * 512, s1);
  lds128_if(impY, ex + w * 512 + 16, s1 + 4);
  if (NEXT) conv_mma<cvs(NEXT, 5), cvs(NEXT, 6)>(dn, da, db);
#pragma unroll
  for (int k = 0; k < 8; k++) {
    const uint32_t s0 = badd2(p0[k], xr[k]);
    e[k] = badd2(pA ? s1[k] : s0, __shfl_sync(0xffffffffu, pA ? s0 : s1[k], src2));
    if (NEXT && k == 3) conv_mma<cvs(NEXT, 6), cvs(NEXT, 7)>(dn, da, db);
  }
  const uint32_t z0 = zs + oo * 4 + (oo / 20) * 240, z1 = zs + (oo + 130) * 4 + ((oo + 130) / 20) * 240;
#pragma unroll
  for (int k = 0; k < 8; k++) asm volatile("st.shared.u32 [%0], %1;" ::"r"((k < 4 ? z0 : z1) + (k & 3) * 80), "r"(e[k]) : "memory");
  asm volatile("fence.proxy.async.shared::cta;" ::: "memory");
  __syncwarp();
  if (lane == 0) mbar_arrive(bar + 8 * (B_SIGZ + ch));
  if (NEXT) { conv_mma<cvs(NEXT, 7), 32>(dn, da, db); wg_commit(); }
}
template <int S, int OWN, int K0 = 0, int K1 = 4> __device__ __forceinline__ void g2_half(float* acc, uint64_t dA, uint64_t dB, int sc) {
#pragma unroll
  for (int kk = K0; kk < K1; kk++)
    wgmma_ss<160, 1, 0>(acc, dA + (((OWN ? slotO(S) : slotF(S)) >> 4) + 128 * kk), dB + (((kk < 2 ? slotB0(S) : slotB1(S)) >> 4) + 2 * (kk & 1)), kk ? 1 : sc);
}

template <int I0, int I1> __device__ __forceinline__ void g2_own(float* acc, uint64_t dA, uint64_t dB) {
  if constexpr (I0 < I1 && I0 < 16) {
    g2_half<((I0 >> 2) + 3) % 5, 1, I0 & 3, (I0 & 3) + 1>(acc, dA, dB, 1);
    g2_own<I0 + 1, I1>(acc, dA, dB);
  }
}

template <int PART> __device__ __forceinline__ void glu_part(const float* acc, uint32_t dst) {
  constexpr int h = PART & 1, aa = PART >> 1;
  uint32_t v[4];
#pragma unroll
  for (int jj = 0; jj < 4; jj++) {
    const int i = 4 * (4 * aa + jj) + 2 * h;
    float t0 = tanh_fast(0.5f * acc[i]), t1 = tanh_fast(0.5f * acc[i + 1]);
    v[jj] = pack_bf16(fmaf(acc[48 + i], t0, acc[48 + i]), fmaf(acc[49 + i], t1, acc[49 + i]));
  }
  asm volatile("stmatrix.sync.aligned.m8n8.x4.shared.b16 [%0], {%1,%2,%3,%4};" ::"r"(dst + h * 1536 + aa * 512), "r"(v[0]), "r"(v[1]), "r"(v[2]), "r"(v[3]) : "memory");
}

struct Params {
  unsigned char c2[72];
  const __nv_bfloat16 *gate_w, *k, *v, *shift_k, *q, *w_gate, *w_up, *w_down, *ssm_k, *ssm_D;
  unsigned char g2[72];
};

enum { mX, mWg, mWu, mU, mQ, mH, mWd, mZ, mO, mK, mV, mCOUNT };
struct Maps { CUtensorMap m[mCOUNT]; };

__global__ void __cluster_dims__(2, 1, 1) __launch_bounds__(384, 1)
fused_kernel(const Params P, const __grid_constant__ Maps M) {
  extern __shared__ __align__(1024) unsigned char sm[];
  const uint32_t sb = smem_u32(sm);
  const uint32_t bar = sb + OFF_BAR;
  const int tid = threadIdx.x, warp = __shfl_sync(0xffffffffu, tid >> 5, 0), lane = tid & 31;
#define CTA_ROLE()                                                                                           \
  const int rank = blockIdx.x & 1;               \
  const int cta = 2 * P.c2[blockIdx.x >> 1] + rank;                                                          \
  const bool has1 = cta < 128;                                                                               \
  const int mb = cta >> 4, ft = cta & 15;                                                        \
  (void)mb; (void)ft;
#define G2_ROLE()                                                                                            \
  const int g2 = P.g2[blockIdx.x >> 1];                                                                      \
  const int db = 2 * (g2 & 7) + rank;                                    \
  const int tb = g2 >> 3;                                                 \
  (void)db; (void)tb;

  if (warp == 0 && P.c2[blockIdx.x >> 1] > 64) __trap();
  if (warp == 4 && elect_one()) {
    prefetch_map(&M.m[mX]);
    prefetch_map(&M.m[mWg]);
    prefetch_map(&M.m[mWu]);
    TS(77);
  }
  if (warp < 8) {
    if (lane == 0) {
#pragma unroll
      for (int j = 0; j < 6; j++) mbar_init(bar + 8 * (B_FULL2 + j) + 48 * warp, (0x44321111u >> (4 * warp)) & 7);
      asm volatile("fence.proxy.async.shared::cta;" ::: "memory");
    }
    __syncwarp();
    asm volatile("setmaxnreg.inc.sync.aligned.u32 224;");
    if (tid == 0) TS(8);
    bar_arrive(1, 384);
    bar_sync(0, 384);
    asm volatile("barrier.cluster.arrive.relaxed.aligned;" ::: "memory");
    CTA_ROLE();
    const int wg = warp >> 2, w = warp & 3;
    const bool elect = (tid & 127) == 0;
    if (tid == 0) TS(11);
    if (has1) {
      const int lane = fresh_lane();
      float acc0[96], acc1[96];
      float *const d0 = acc0, *const d1 = acc1;
      {
        const uint64_t dA = mkdesc(G1SB + wg * 16384, 16, 1024, 1);
        const uint64_t dB = mkdesc(G1SB + 32768, 4096, 512, 2);
#pragma unroll 1
        for (int kb = 0; kb < 8; kb++) {
          const int rg = (kb + 1) % 3;
          const uint64_t da = dA + rg * (G1_STAGE >> 4), db = dB + rg * (G1_STAGE >> 4);
          if (tid == 0 && kb >= 6) TSB(70 + kb);
          mbar_wait(bar + 8 * (B_FULL1 + rg), (kb / 3) & 1);
          if (tid == 0) TS(kb == 0 ? 1 : 46 + kb);
          wg_fence();
#pragma unroll
          for (int kk = 0; kk < REL; kk++) wgmma_ss<192, 0, 1>(acc0, da + 2 * kk, db + 64 * kk, (kb | kk) != 0);
          wg_commit();
          wg_wait<1>();
          if (kb > 0 && elect) mbar_arrive(bar + 8 * (B_EMPTY1 + kb % 3));
          wg_fence();
#pragma unroll
          for (int kk = REL; kk < 4; kk++) wgmma_ss<192, 0, 1>(acc0, da + 2 * kk, db + 64 * kk, 1);
#pragma unroll
          for (int kk = 0; kk < 4; kk++) wgmma_ss<192, 0, 1>(acc1, da + 512 + 2 * kk, db + 64 * kk, (kb | kk) != 0);
          wg_commit();
        }
#define G1_MMA(ACC, J) wgmma_ss<192, 0, 1>(ACC == 0 ? acc0 : acc1, dA + (((J) >> 2) * (G1_STAGE >> 4) + ACC * 512 + 2 * ((J) & 3)), dB + (((J) >> 2) * (G1_STAGE >> 4) + 64 * ((J) & 3)), 1)
        if (tid == 0) TS(124);
        mbar_wait(bar + 8 * (B_FULL1 + 0), 0);
        if (tid == 0) TS(125);
        wg_fence();
#pragma unroll
        for (int j = 0; j < REL; j++) G1_MMA(0, j);
        wg_commit();
        wg_wait<1>();
        if (elect) mbar_arrive(bar + 8 * B_R2FREE);
        wg_fence();
#pragma unroll
        for (int j = REL; j < 4; j++) G1_MMA(0, j);
#pragma unroll
        for (int j = 0; j < TLA; j++) G1_MMA(1, j);
        if (tid == 0) TS(46);
        mbar_wait(bar + 8 * (B_FULL1 + 1), 1);
        if (tid == 0) TS(95);
        wg_fence();
#pragma unroll
        for (int j = 4; j < 8; j++) G1_MMA(0, j);
        wg_commit();
#pragma unroll
        for (int j = TLA; j < TLA + 2; j++) G1_MMA(1, j);
        wg_commit();
        const uint32_t hd = sb + (w >> 1) * G1_STAGE + wg * 16384 + (w & 1) * 3072 + (lane & 7) * 64 + (((lane >> 3) ^ ((lane & 7) >> 1)) << 4);
        mbar_wait(bar + 8 * B_GATE, 0);
        wg_wait<1>();
        pin<96>(acc0);
        if (elect) TS(2 + wg);
        wg_fence();
        if (TLA + 2 < 8) G1_MMA(1, TLA + 2);
        glu_part<0>(acc0, hd);
        if (TLA + 3 < 8) G1_MMA(1, TLA + 3);
        glu_part<1>(acc0, hd);
        if (TLA + 4 < 8) G1_MMA(1, TLA + 4);
        glu_part<2>(acc0, hd);
        if (TLA + 5 < 8) G1_MMA(1, TLA + 5);
        glu_part<3>(acc0, hd);
        if (TLA + 6 < 8) G1_MMA(1, TLA + 6);
        glu_part<4>(acc0, hd);
        if (TLA + 7 < 8) G1_MMA(1, TLA + 7);
        wg_commit();
        glu_part<5>(acc0, hd);
        asm volatile("fence.proxy.async.shared::cta;" ::: "memory");
        __syncwarp();
        if (lane == 0) mbar_arrive(bar + 8 * (B_SIGH + 2 * wg));
        if (elect) TSB(6 + wg);
        const uint64_t ca = conv_da(wg), cb = conv_db(wg);
        mbar_wait(bar + 8 * (B_UFULL + wg), 0);
        if (elect) TS(10 + 3 * wg);
        wg_fence();
        conv_mma<0, CV0>(d0, ca, cb);
        wg_commit();
        wg_wait<1>();
        pin<96>(acc1);
        if (elect) mbar_arrive(bar + 8 * B_G1DONE);
        wg_fence();
        constexpr int gs[7] = {GL1};
        conv_mma<CV0 + gs[0], CV0 + gs[1]>(d0, ca, cb);
        glu_part<0>(acc1, hd + 8192);
        conv_mma<CV0 + gs[1], CV0 + gs[2]>(d0, ca, cb);
        glu_part<1>(acc1, hd + 8192);
        conv_mma<CV0 + gs[2], CV0 + gs[3]>(d0, ca, cb);
        glu_part<2>(acc1, hd + 8192);
        conv_mma<CV0 + gs[3], CV0 + gs[4]>(d0, ca, cb);
        glu_part<3>(acc1, hd + 8192);
        conv_mma<CV0 + gs[4], CV0 + gs[5]>(d0, ca, cb);
        glu_part<4>(acc1, hd + 8192);
        conv_mma<CV0 + gs[5], CV0 + gs[6]>(d0, ca, cb);
        glu_part<5>(acc1, hd + 8192);
        asm volatile("fence.proxy.async.shared::cta;" ::: "memory");
        __syncwarp();
        if (lane == 0) mbar_arrive(bar + 8 * (B_SIGH + 2 * wg + 1));
        if (elect) TS(4 + wg);
        conv_mma<CV0 + gs[6], 32>(d0, ca, cb);
        wg_commit();
      }
      {
        const uint64_t ca = conv_da(wg + 2), cb = conv_db(wg + 2);
        mbar_wait(bar + 8 * (B_UFULL + wg + 2), 0);
        if (elect) TS(16 + 3 * wg);
        wg_fence();
        conv_mma<0, CV0>(d1, ca, cb);
        wg_commit();
        wg_wait<1>();
        pin<64>(d0);
        if (elect) TSB(11 + 3 * wg);
        wg_fence();
        conv_finish<1>(d0, sb, bar, wg, wg, w, d1, ca, cb);
        if (elect) TS(12 + 3 * wg);
      }
      if (wg == 0) {
        const uint64_t ca = conv_da(4), cb = conv_db(4);
        mbar_wait(bar + 8 * (B_UFULL + 4), 0);
        if (elect) TS(22);
        wg_fence();
        conv_mma<0, CV0>(d0, ca, cb);
        wg_commit();
        wg_wait<1>();
        pin<64>(d1);
        if (elect) TSB(17);
        wg_fence();
        conv_finish<2>(d1, sb, bar, 2, wg, w, d0, ca, cb);
        if (elect) TS(18);
        wg_wait<0>();
        pin<64>(d0);
        if (elect) TS(23);
        conv_finish<0>(d0, sb, bar, 4, wg, w, d0, ca, cb);
        if (elect) TS(24);
      } else {
        wg_wait<0>();
        pin<64>(d1);
        if (elect) TS(20);
        conv_finish<0>(d1, sb, bar, 3, wg, w, d1, 0, 0);
        if (elect) TS(21);
      }
    }
    const int lane = fresh_lane();
    const uint32_t xo = w * 512 + lane * 16;
    if (wg == 1) {
      float accF[80], accO[80];
      const uint64_t dA = mkdesc(SB0, 1024, 1024, 1);
      const uint64_t dB = mkdesc(SB0, 16, 512, 2);
#define G2_STAGE(S)                                                              \
      if (elect) TS(80 + 5 * r + S);                                             \
      mbar_wait(bar + 8 * (B_FULL2 + S), r);                                     \
      if (elect) TS(64 + 5 * r + S);                                             \
      wg_fence();                                                                \
      g2_half<S, 0, 0, REL2>(accF, dA, dB, (r | S) != 0);                        \
      wg_commit();                                                               \
      wg_wait<1>();                                                              \
      if ((r | S) != 0 && elect) mbar_arrive(bar + 8 * (B_EMPTY2 + (S + 4) % 5)); \
      wg_fence();                                                                \
      g2_half<S, 0, REL2, 4>(accF, dA, dB, 1);                                   \
      g2_half<S, 1>(accO, dA, dB, (r | S) != 0);                                 \
      wg_commit();
#pragma unroll 1
      for (int r = 0; r < 2; r++) {
        G2_STAGE(0) G2_STAGE(1) G2_STAGE(2)
        if (r) break;
        G2_STAGE(3) G2_STAGE(4)
      }
      uint32_t av[40], om[20], p[40];
      mbar_wait(bar + 8 * (B_FULL2 + 3), 1);
      if (elect) TS(72);
      wg_fence();
      g2_half<3, 0, 0, REL2>(accF, dA, dB, 1);
      wg_commit();
      wg_wait<1>();
      if ((tid & 126) == 0) mbar_arrive(bar + 8 * B_ZF);
      wg_fence();
      g2_half<3, 0, REL2, 4>(accF, dA, dB, 1);
      g2_own<0, TM8>(accO, dA, dB);
      mbar_wait(bar + 8 * (B_FULL2 + 4), 1);
      if (elect) TS(73);
      wg_fence();
      g2_half<4, 0>(accF, dA, dB, 1);
      g2_own<TM8, TM9>(accO, dA, dB);
      mbar_wait(bar + 8 * (B_FULL2 + 0), 0);
      if (elect) TS(74);
      wg_fence();
      g2_half<0, 0>(accF, dA, dB, 1);
      g2_own<TM9, TM10>(accO, dA, dB);
      mbar_wait(bar + 8 * B_QG, 0);
#pragma unroll
      for (int j = 0; j < 20; j++) asm volatile("ld.shared.u32 %0, [%1];" : "=r"(om[j]) : "r"(sb + OFF_G + j * 32 + 16 + 4 * (lane & 3)) : "memory");
      mbar_wait(bar + 8 * B_XF, 0);
      mbar_wait(bar + 8 * (B_FULL2 + 1), 0);
      if (elect) TS(75);
      wg_fence();
      g2_half<1, 0>(accF, dA, dB, 1);
      wg_commit();
      g2_own<TM10, TM10 + 2>(accO, dA, dB);
      wg_commit();
      {
        const uint32_t xd = peer_addr(sb + OFF_XCH + xo), xb = peer_addr(bar + 8 * B_XCH);
        const int i8 = lane & 7, mi = lane >> 3;
        const uint32_t oa = sb + OFF_OUT + ((mi >> 1) * 8 + i8) * 128 + (((2 * w + (mi & 1)) ^ i8) << 4);
        wg_wait<1>();
        pin<80>(accF);
        if (elect) TS(36);
        wg_fence();
#define G2_SEND(I)                                                                                                                                  \
        asm volatile("st.async.shared::cluster.mbarrier::complete_tx::bytes.v4.b32 [%0], {%1,%2,%3,%4}, [%5];" ::"r"(xd + (I) * 2048),              \
                     "r"(pack_bf16(accF[8 * (I)], accF[8 * (I) + 1])), "r"(pack_bf16(accF[8 * (I) + 2], accF[8 * (I) + 3])),                        \
                     "r"(pack_bf16(accF[8 * (I) + 4], accF[8 * (I) + 5])), "r"(pack_bf16(accF[8 * (I) + 6], accF[8 * (I) + 7])),                    \
                     "r"(xb + ((I) / 5) * 8) : "memory");                                                                                           \
        g2_own<TM10 + 2 + (I) * SPN / SPD, TM10 + 2 + ((I) + 1) * SPN / SPD>(accO, dA, dB);
        G2_SEND(0) G2_SEND(1) G2_SEND(2) G2_SEND(3) G2_SEND(4)
        static_assert(TM10 + 2 + 5 * SPN / SPD >= 4, "");
        wg_commit();
        G2_SEND(5) G2_SEND(6) G2_SEND(7) G2_SEND(8) G2_SEND(9)
        if (elect) TS(37);
        constexpr int N1 = TM10 + 2 + 10 * SPN / SPD;
        g2_own<N1, 16 - AVL>(accO, dA, dB);
        wg_commit();
        wg_wait<1>();
        wg_fence();
        __syncwarp();
        bar_sync(6, 256);
        if (elect) TS(78);
#pragma unroll
        for (int i = 0; i < 10; i++)
          asm volatile("ld.shared.v4.u32 {%0,%1,%2,%3}, [%4];" : "=r"(av[4 * i]), "=r"(av[4 * i + 1]), "=r"(av[4 * i + 2]), "=r"(av[4 * i + 3]) : "r"(sb + OFF_Z + w * 5120 + lane * 16 + i * 512) : "memory");
        g2_own<(N1 > 16 - AVL ? N1 : 16 - AVL), 16>(accO, dA, dB);
        wg_commit();
        if (elect) TS(38);
#pragma unroll
        for (int hf = 0; hf < 2; hf++) {
          if (hf == 0 || !P1E) {
            mbar_wait(bar + 8 * (B_XCH + hf), 0);
            if (elect) TS(hf ? 59 : 31);
#pragma unroll
            for (int i = 5 * hf; i < 5 * hf + 5; i++)
              asm volatile("ld.shared.v4.u32 {%0,%1,%2,%3}, [%4];" : "=r"(p[4 * i]), "=r"(p[4 * i + 1]), "=r"(p[4 * i + 2]), "=r"(p[4 * i + 3]) : "r"(sb + OFF_XCH + xo + i * 2048) : "memory");
          }
          if (hf == 0 && P1E) {
            mbar_wait(bar + 8 * (B_XCH + 1), 0);
            if (elect) TS(59);
#pragma unroll
            for (int i = 5; i < 10; i++)
              asm volatile("ld.shared.v4.u32 {%0,%1,%2,%3}, [%4];" : "=r"(p[4 * i]), "=r"(p[4 * i + 1]), "=r"(p[4 * i + 2]), "=r"(p[4 * i + 3]) : "r"(sb + OFF_XCH + xo + i * 2048) : "memory");
          }
          if (hf == 0) {
            wg_wait<0>();
            pin<80>(accO);
            if (elect) TS(28);
          }
#pragma unroll
          for (int i = 20 * hf; i < 20 * hf + 20; i++) p[i] = bfma2(badd2(pack_bf16(accO[2 * i], accO[2 * i + 1]), p[i]), om[i >> 1], av[i]);
#pragma unroll
          for (int i = 5 * hf; i < 5 * hf + 5; i++)
            asm volatile("stmatrix.sync.aligned.m8n8.x4.trans.shared.b16 [%0], {%1,%2,%3,%4};" ::"r"(oa + i * 2048), "r"(p[4 * i]), "r"(p[4 * i + 1]), "r"(p[4 * i + 2]), "r"(p[4 * i + 3]) : "memory");
          asm volatile("fence.proxy.async.shared::cta;" ::: "memory");
          if (elect) TS(57 + hf);
          __syncwarp();
          bar_arrive(8 + hf, 160);
        }
      }
    } else {
      G2_ROLE();
      const int q = lane & 3, i8 = lane & 7, mi = lane >> 3;
      const uint32_t qa = sb + OFF_Q + ((mi >> 1) * 8 + i8) * 128 + (((2 * w + (mi & 1)) ^ i8) << 4);
      const uint32_t za = sb + OFF_Z + (16 * w + (lane >> 2)) * 320 + q * 80;
      uint32_t qv[40], av[40];
      mbar_wait(bar + 8 * B_QG, 0);
#pragma unroll
      for (int jp = 0; jp < 10; jp++)
        asm volatile("ldmatrix.sync.aligned.m8n8.x4.trans.shared.b16 {%0,%1,%2,%3}, [%4];" : "=r"(qv[4 * jp]), "=r"(qv[4 * jp + 1]), "=r"(qv[4 * jp + 2]), "=r"(qv[4 * jp + 3]) : "r"(qa + jp * 2048) : "memory");
#pragma unroll
      for (int j = 0; j < 20; j++) {
        const uint32_t g2 = *reinterpret_cast<const uint32_t*>(sm + OFF_G + j * 32 + 4 * q);
        qv[2 * j] = bmul2(qv[2 * j], g2);
        qv[2 * j + 1] = bmul2(qv[2 * j + 1], g2);
      }
#pragma unroll
      for (int i = 0; i < 40; i++) asm volatile("" : "+r"(qv[i])::"memory");
      __syncwarp();
      if (lane == 0) mbar_arrive(bar + 8 * B_QC);
      if (elect) TS(60);
      mbar_wait(bar + 8 * B_Z, 0);
      if (elect) TS(27);
#pragma unroll
      for (int i = 0; i < 10; i++)
        asm volatile("ld.shared.v4.u32 {%0,%1,%2,%3}, [%4];" : "=r"(av[8 * (i >> 1) + (i & 1)]), "=r"(av[8 * (i >> 1) + 2 + (i & 1)]), "=r"(av[8 * (i >> 1) + 4 + (i & 1)]), "=r"(av[8 * (i >> 1) + 6 + (i & 1)])
                     : "r"(za + (i & 1) * 2560 + (i >> 1) * 16) : "memory");
#pragma unroll
      for (int i = 0; i < 40; i++) av[i] = bmul2(av[i], qv[i]);
      __syncwarp();
#pragma unroll
      for (int i = 0; i < 10; i++)
        asm volatile("st.shared.v4.b32 [%0], {%1,%2,%3,%4};" ::"r"(sb + OFF_Z + w * 5120 + lane * 16 + i * 512), "r"(av[4 * i]), "r"(av[4 * i + 1]), "r"(av[4 * i + 2]), "r"(av[4 * i + 3]) : "memory");
      if (elect) TS(29);
      __syncwarp();
      bar_arrive(6, 256);
      if (w == 0) {
#pragma unroll
        for (int hf = 0; hf < 2; hf++) {
          bar_sync(8 + hf, 160);
          if (elect_one()) tma4_store(&M.m[mO], sb + OFF_OUT + hf * 10240, db * 64, 0, ((2 * tb + hf) % 13) * 10, (2 * tb + hf) / 13);
          __syncwarp();
        }
        if (elect) TS(26);
        asm volatile("cp.async.bulk.commit_group;" ::: "memory");
        asm volatile("cp.async.bulk.wait_group.read 0;" ::: "memory");
      }
      if (elect) {
        TS(30);
      }
    }
  } else {
    asm volatile("setmaxnreg.dec.sync.aligned.u32 56;");
    if (warp == 8 && lane == 0) {
#pragma unroll
      for (int rg = 0; rg < 3 + !KVLD; rg++) mbar_init(bar + 8 * (B_FULL1 + rg), 1);
#pragma unroll
      for (int rg = 0; rg < 3; rg++) mbar_expect(bar + 8 * (B_FULL1 + rg), G1_STAGE + (rg == 1 ? 1280 - (S0M ? 24576 : 0) : 0));
      if (!KVLD) mbar_expect(bar + 8 * B_KV, 23040 + 21760 + 640);
      asm volatile("fence.proxy.async.shared::cta;" ::: "memory");
      TS(76);
    }
    __syncwarp();
    bar_arrive(warp == 8 ? 0 : 1, 384);
    if (warp != 8) bar_sync(0, 384);
    CTA_ROLE();
    if (warp == 8) {
      if (has1 && elect_one()) {
        TS(126);
#define G1_LOAD(KB, RG)                                                                                              \
        tma4(sb + (RG) * G1_STAGE, &M.m[mX], (KB) * 64, 0, (mb & 3) * 32, mb >> 2, bar + 8 * (B_FULL1 + (RG)));      \
        tma3(sb + (RG) * G1_STAGE + 32768, &M.m[mWg], 0, (KB) * 64, ft * 3, bar + 8 * (B_FULL1 + (RG)));             \
        tma3(sb + (RG) * G1_STAGE + 45056, &M.m[mWu], 0, (KB) * 64, ft * 3, bar + 8 * (B_FULL1 + (RG)));
        G1_LOAD(0, 1);
        TS(127);
      }
      if (has1 && elect_one()) {
        bulk_g2s(sb + OFF_EX + 640, P.gate_w, 1280, bar + 8 * (B_FULL1 + 1));
        G1_LOAD(1, 2);
        G1_LOAD(2, 0);
        TS(6);
      }
      __syncwarp();
      bar_sync(1, 384);
    } else if (elect_one()) {
      prefetch_map(&M.m[warp == 9 ? mU : warp - 5]);
    }
    if (lane == 0 && warp < 10) TS(warp == 8 ? 14 : 17);
    __syncwarp();
    if (warp != 11) asm volatile("barrier.cluster.arrive.relaxed.aligned;" ::: "memory");
    if (warp == 8) {
      if (has1) {
#define V_COPY() tma3(sb + OFF_V, &M.m[mV], (cta & 7) * 80, (cta >> 3) * 16 - 1, 0, bar + 8 * B_KV);
#define KV_COPY()                                                                                    \
          tma3(sb + OFF_H, &M.m[mK], (cta & 7) * 80, (cta >> 3) * 16 - 2, 0, bar + 8 * B_KV);             \
          if (VAT <= KVAT) { V_COPY() }                                                                \
          bulk_g2s(sb + OFF_EX, P.shift_k + (cta & 7) * 320, 640, bar + 8 * B_KV);
        if (elect_one()) {
          KV_COPY();
        }
        float s[4] = {0.f, 0.f, 0.f, 0.f};
        const uint32_t xa = sb + ft * 2048 + (lane >> 3) * 128;
#pragma unroll 1
        for (int kb = 2; kb < 12; kb++) {
          const int kg = kb - 2, rg = (kb - 1) % 3;
          if (kb >= 3 && kb < 10) {
            const int rl = (kb + 1) % 3;
            const uint32_t dst = sb + rl * G1_STAGE, fb = bar + 8 * (B_FULL1 + rl);
            mbar_wait_t(bar + 8 * (B_EMPTY1 + rl), (kb / 3 - 1) & 1);
            if (elect_one()) {
              tma4(dst, &M.m[mX], kb * 64, 0, (mb & 3) * 32, mb >> 2, fb);
              tma3(dst + 32768, &M.m[mWg], 0, kb * 64, ft * 3, fb);
              tma3(dst + 32768 + 12288, &M.m[mWu], 0, kb * 64, ft * 3, fb);
              if (kb == KVAT) { KV_COPY(); }
              if (VAT > KVAT && kb == VAT) { V_COPY(); }
              TS(85 + kb);
            }
          } else {
            mbar_wait_t(bar + 8 * (B_FULL1 + rg), (kg / 3) & 1);
          }
          uint4 xv[4], gw;
#pragma unroll
          for (int i = 0; i < 4; i++)
            asm volatile("ld.shared.v4.u32 {%0,%1,%2,%3}, [%4];" : "=r"(xv[i].x), "=r"(xv[i].y), "=r"(xv[i].z), "=r"(xv[i].w)
                         : "r"(xa + rg * G1_STAGE + i * 512 + (((lane & 7) ^ ((lane >> 3) + 4 * (i & 1))) << 4)) : "memory");
          asm volatile("ld.shared.v4.u32 {%0,%1,%2,%3}, [%4];" : "=r"(gw.x), "=r"(gw.y), "=r"(gw.z), "=r"(gw.w) : "r"(sb + OFF_EX + 640 + kg * 128 + (lane & 7) * 16) : "memory");
          if (lane == 0 && kg < 7) mbar_expect(bar + 8 * (B_FULL1 + rg), G1_STAGE);
          if (kb == PFK && elect_one()) bulk_prefetch(P.ssm_k + (size_t)cta * 5 * 2048, 20480);
          if (kb == PFW && elect_one()) bulk_prefetch(P.w_down + (size_t)cta * 7680, 15360);
#pragma unroll
          for (int i = 0; i < 4; i++) {
            const uint32_t p0 = bmul2(xv[i].x, gw.x), p1 = bmul2(xv[i].y, gw.y), p2 = bmul2(xv[i].z, gw.z), p3 = bmul2(xv[i].w, gw.w);
            s[i] += (bflo(p0) + bfhi(p0)) + (bflo(p1) + bfhi(p1)) + ((bflo(p2) + bfhi(p2)) + (bflo(p3) + bfhi(p3)));
          }
          pin<4>(s);
          __syncwarp();
          if (kg == 7 && lane == 0) mbar_arrive(bar + 8 * B_R2FREE);
        }
        if (lane == 0) { mbar_arrive(bar + 8 * B_GATE); TS(44); }
        float s0 = (lane & 4) ? s[2] : s[0], s1 = (lane & 4) ? s[3] : s[1];
        s0 += __shfl_xor_sync(0xffffffffu, (lane & 4) ? s[0] : s[2], 4);
        s1 += __shfl_xor_sync(0xffffffffu, (lane & 4) ? s[1] : s[3], 4);
        float sv = (lane & 2) ? s1 : s0;
        sv += __shfl_xor_sync(0xffffffffu, (lane & 2) ? s0 : s1, 2);
        sv += __shfl_xor_sync(0xffffffffu, sv, 1);
        sv = __bfloat162float(__float2bfloat16(sv));
        sv = __bfloat162float(__float2bfloat16(1.f / (1.f + __expf(-sv))));
        reinterpret_cast<__nv_bfloat16*>(sm + OFF_GS)[(lane & 4) * 4 + (lane & 1) * 8 + (lane & 2) * 2 + (lane >> 3)] = __float2bfloat16((lane & 1) ? 0.5f - 0.5f * sv : sv);
        asm volatile("fence.proxy.async.shared::cta;" ::: "memory");
        __syncwarp();
        if (lane == 0) mbar_arrive(bar + 8 * B_GS);
        mbar_wait_t(bar + 8 * B_R2FREE, 0);
      }
      G2_ROLE();
#pragma unroll 1
      for (int r = 0; r < 3; r++) {
#pragma unroll
        for (int s = 0; s < 5; s++) {
          const uint32_t fb = bar + 8 * (B_FULL2 + s);
          if (s == 2 && r == 2) break;
          if (r) mbar_wait_t(bar + 8 * (B_EMPTY2 + s), r >> 1);
          else if (s == 1 && has1) mbar_wait_t(bar + 8 * B_G1DONE, 0);
          else if (s == 4 && has1) { mbar_wait_t(bar + 8 * (B_CD + 2), 0); mbar_wait_t(bar + 8 * B_Z3, 0); }
          if (elect_one()) {
            mbar_expect(fb, 36864);
            tma3(sb + slotF(s), &M.m[mWd], 0, rank * 768 + r * 320 + s * 64, db ^ 1, fb);
            tma3(sb + slotO(s), &M.m[mWd], 0, rank * 768 + r * 320 + s * 64, db, fb);
            TS(96 + 5 * r + s);
          }
        }
      }
    } else {
      const int hw = warp - 9;
      if ((sb & 0x3FFFF) != SB0) __trap();
      if (hw == 2) {
        if (lane == 0) { mbar_expect(bar + 8 * B_XCH, 10240); mbar_expect(bar + 8 * (B_XCH + 1), 10240); }
        __syncwarp();
        asm volatile("barrier.cluster.arrive.release.aligned;\nbarrier.cluster.wait.acquire.aligned;" ::: "memory");
      }
      if (has1) {
      {
        const int cq = lane & 3, gl = hw < 2 ? (((tid - 288) >> 2) ^ ((cq & 2) << 1)) + 1 : 0;
        const int cl = hw < 2 ? 0 : lane >> 2;
        uint32_t kp = sb + OFF_H + gl * 160 + cq * 8 + cl * 32, wp = sb + OFF_EX + cq * 32 + cl * 128;
        const uint32_t u1 = sb + OFF_US + cq * 2048 + (15 - gl) * 16, u2 = u1 + 24;
        const uint32_t ua = (cq & 1) && hw < 2 ? u2 : u1, ub = (cq & 1) ? u1 : u2;
        const bool pa0 = (cq & 1) || gl <= 15, pb0 = !(cq & 1) || gl <= 15;
        uint2 vr[8], kr[11];
        uint4 sa, sc;
#define KV_LOAD_K()                                                                                                                                   \
        asm volatile("ld.volatile.shared.v4.u32 {%0,%1,%2,%3}, [%4];" : "=r"(sa.x), "=r"(sa.y), "=r"(sa.z), "=r"(sa.w) : "r"(wp) : "memory");       \
        asm volatile("ld.volatile.shared.v4.u32 {%0,%1,%2,%3}, [%4];" : "=r"(sc.x), "=r"(sc.y), "=r"(sc.z), "=r"(sc.w) : "r"(wp + 16) : "memory");  \
        _Pragma("unroll") for (int r = 0; r < 3; r++) kr[r] = lds64(kp + (r + 5) * 18 * 160);                                                        \
        _Pragma("unroll") for (int r = 0; r < KVA; r++) kr[r + 3] = lds64(kp + (r * 18 + 1) * 160);
#define KV_LOAD_V()                                                                                                                                   \
        _Pragma("unroll") for (int r = KVA; r < 8; r++) kr[r + 3] = lds64(kp + (r * 18 + 1) * 160);                                                  \
        _Pragma("unroll") for (int r = 0; r < KVB; r++) vr[r] = lds64(kp + 23040 + r * 17 * 160);
#define KV_COMPUTE()                                                                                                                                  \
        {                                                                                                                                             \
          const uint32_t wa[4] = {__byte_perm(sa.x, sa.z, 0x5410), __byte_perm(sa.x, sa.z, 0x7632), __byte_perm(sa.y, sa.w, 0x5410), __byte_perm(sa.y, sa.w, 0x7632)}; \
          const uint32_t wb[4] = {__byte_perm(sc.x, sc.z, 0x5410), __byte_perm(sc.x, sc.z, 0x7632), __byte_perm(sc.y, sc.w, 0x5410), __byte_perm(sc.y, sc.w, 0x7632)}; \
          _Pragma("unroll") for (int r = 0; r < 8; r++) {                                                                                             \
            uint32_t x = bmul2(kr[r].x, wa[3]), y = bmul2(kr[r].y, wb[3]);                                                                            \
            if (r + KVB < 8) vr[r + KVB] = lds64(kp + 23040 + (r + KVB) * 17 * 160);                                                                  \
            _Pragma("unroll") for (int j = 1; j < 4; j++) {                                                                                           \
              x = bfma2(kr[r + j].x, wa[3 - j], x);                                                                                                   \
              y = bfma2(kr[r + j].y, wb[3 - j], y);                                                                                                   \
            }                                                                                                                                         \
            vr[r].x = bmul2(x, vr[r].x);                                                                                                              \
            vr[r].y = bmul2(y, vr[r].y);                                                                                                              \
          }                                                                                                                                           \
        }
#define KV_STORE(PA, PB)                                                                                                                              \
        _Pragma("unroll") for (int cc = 0; cc < 4; cc++) {                                                                                            \
          const uint32_t sel = (cc & 1) ? 0x7632 : 0x5410;                                                                                            \
          _Pragma("unroll") for (int p = 0; p < 2; p++) {                                                                                             \
            const int r = 4 - 4 * p;                                                                                                                  \
            const uint32_t qx = (cc & 2) ? __byte_perm(vr[r].y, vr[r + 1].y, sel) : __byte_perm(vr[r].x, vr[r + 1].x, sel);                           \
            const uint32_t qy = (cc & 2) ? __byte_perm(vr[r + 2].y, vr[r + 3].y, sel) : __byte_perm(vr[r + 2].x, vr[r + 3].x, sel);                   \
            if (PA) asm volatile("st.shared.v2.u32 [%0], {%1,%2};" ::"r"(ua + cc * 512 + p * 256), "r"(qx), "r"(qy) : "memory");                      \
            if (PB) asm volatile("st.shared.v2.u32 [%0], {%1,%2};" ::"r"(ub + cc * 512 + p * 256), "r"(qx), "r"(qy) : "memory");                      \
          }                                                                                                                                           \
        }                                                                                                                                             \
        asm volatile("fence.proxy.async.shared::cta;" ::: "memory");
        mbar_wait_t(bar + 8 * B_KV, 0);
        if (hw == 0 && lane == 0) TS(39);
        KV_LOAD_K();
        KV_LOAD_V();
        if (hw < 2) {
#pragma unroll 1
          for (int cb = 0; cb < 5; cb++) {
            if (cb == KVTS && lane == 0) TS(108);
            KVX_AT(0);
            KV_COMPUTE();
            kp += 32;
            wp += 128;
            KV_LOAD_K();
            if (cb == KVTS && lane == 0) TS(109);
            KVX_AT(1);
            bar_sync(5, 96);
            if (cb == KVTS && lane == 0) TS(110);
            KVX_AT(2);
            KV_STORE(pa0, pb0);
            if (cb == KVTS && lane == 0) TS(111);
            KVX_AT(3);
            KV_LOAD_V();
            __syncwarp();
            bar_arrive(7, 96);
            if (cb == KVTS && lane == 0) TS(9);
            KVX_AT(4);
          }
        } else {
          KV_COMPUTE();
#pragma unroll 1
          for (int cb = 0; cb < 5; cb++) {
            asm volatile("cp.async.bulk.wait_group.read 0;" ::: "memory");
            bar_sync(5, 96);
            if (cb == 4 && elect_one()) {
              mbar_expect(bar + 8 * B_HLD, 20480);
#pragma unroll
              for (int ch = 0; ch < 5; ch++)
                bulk_g2s(sb + OFF_H + (2 * ch + 1) * H_PITCH + 224, P.ssm_k + (size_t)(cta * 5 + ch) * 2048, 4096, bar + 8 * B_HLD);
            }
            KV_STORE(cl == cb, false);
            __syncwarp();
            bar_sync(7, 96);
            if (elect_one()) tma2_store(&M.m[mU], sb + OFF_US, 1920 - 128 * (cta >> 3), (cta & 7) * 160 + cb * 32);
            asm volatile("cp.async.bulk.commit_group;" ::: "memory");
          }
        }
        if (lane == 0) TS(54 + hw);
        if (hw == 2) {
          asm volatile("cp.async.bulk.wait_group 0;" ::: "memory");
          __syncwarp();
          if (lane == 0) { flag_add(&g_cnt[(C_U + (cta & 7)) * 32]); TS(40); }
          flag_wait(&g_cnt[(C_U + mb) * 32], &g_cnt[(C_U + mb) * 32], 16);
          if (lane == 0) TS(32);
          mbar_wait_t(bar + 8 * B_R2FREE, 0);
          if (elect_one()) {
#pragma unroll
            for (int ch = 0; ch < 5; ch++) {
              mbar_expect(bar + 8 * (B_UFULL + ch), 8192 + (FCP ? 4080 : 0));
              bulk_g2s(sb + OFF_U + (4 - ch) * 8192, g_U + (size_t)(5 * cta + ch) * 4096, 8192, bar + 8 * (B_UFULL + ch));
            }
            TS(33);
          }
        }
      }
      if (hw < 2) {
        int ht;
        asm volatile("mov.u32 %0, %%tid.x;" : "=r"(ht));
        ht -= 288;
        const int lane = ht & 31;
        for (int i = ht; i < 10 * 15; i += 64) {
          const int b = i / 15, e = i % 15;
          if (e < 14) *reinterpret_cast<uint4*>(sm + OFF_H + b * H_PITCH + e * 16) = make_uint4(0u, 0u, 0u, 0u);
          else if ((b & 1) == 0) *reinterpret_cast<uint2*>(sm + OFF_H + b * H_PITCH + 224) = make_uint2(0u, 0u);
        }
        const float dv = lane < 5 ? __bfloat162float(P.ssm_D[cta * 5 + lane]) : 0.f;
        __syncwarp();
        mbar_wait_t(bar + 8 * B_HLD, 0);
        if (hw == 0) {
          if (lane < 5) {
            __nv_bfloat16* h0 = reinterpret_cast<__nv_bfloat16*>(sm + OFF_H + (2 * lane + 1) * H_PITCH + 224);
            *h0 = __float2bfloat16(__bfloat162float(*h0) + dv);
          }
          __syncwarp();
        }
#pragma unroll 1
        for (int b = 0; b < 5; b++) {
          unsigned char* dst = sm + OFF_H + b * 2 * H_PITCH + (ht & 32) * 64 + 232 + lane * 8;
          uint2 hv[8];
#pragma unroll
          for (int u = 0; u < 8; u++) hv[u] = *reinterpret_cast<const uint2*>(dst + H_PITCH - 8 + u * 256);
#pragma unroll
          for (int u = 0; u < 8; u++) *reinterpret_cast<uint2*>(dst + u * 256) = hv[u];
          asm volatile("fence.proxy.async.shared::cta;" ::: "memory");
          __syncwarp();
          if (lane == 0) mbar_arrive(bar + 8 * (B_UFULL + b));
        }
        if (hw == 1 && lane == 0) TS(41);
      }
      }
      G2_ROLE();
      const int ga = 20 * tb, gb = ga + 19;
      const unsigned* fa = &g_cnt[(C_H + 2 * ((ga / 130) * 4 + min((ga % 130) >> 5, 3))) * 32];
      const unsigned* fb = &g_cnt[(C_H + 2 * ((gb / 130) * 4 + min((gb % 130) >> 5, 3))) * 32];
      if (hw == 0) {
        const __nv_bfloat16* hsrc = g_Hs + (size_t)(rank * 24 * NGRP + ga) * 256;
        if (has1) mbar_wait_t(bar + 8 * B_HDR, 0);
        if (lane == 0) TS(25);
        flag_wait(fa + rank * 32, fb + rank * 32, 8);
        if (lane == 0) TS(34);
#pragma unroll 1
        for (int r = 0; r < 3; r++) {
#pragma unroll
          for (int s = 0; s < 5; s++) {
            if (s == 2 && r == 2) break;
            if (r) mbar_wait_t(bar + 8 * (B_EMPTY2 + s), r >> 1);
            else if (s == 3 && has1) { mbar_wait_t(bar + 8 * (B_CD + 0), 0); mbar_wait_t(bar + 8 * (B_CD + 1), 0); }
            else if (s == 4 && has1) mbar_wait_t(bar + 8 * (B_CD + 2), 0);
            if (elect_one()) {
              bulk_g2s(sb + slotB0(s), hsrc + s * (2 * NGRP * 256), 10240, bar + 8 * (B_FULL2 + s));
              bulk_g2s(sb + slotB1(s), hsrc + s * (2 * NGRP * 256) + NGRP * 256, 10240, bar + 8 * (B_FULL2 + s));
              TS(112 + 5 * r + s);
            }
          }
          hsrc += 10 * NGRP * 256;
        }
      } else if (hw == 1) {
        if (elect_one()) { prefetch_map(&M.m[mQ]); prefetch_map(&M.m[mZ]); prefetch_map(&M.m[mO]); }
        flag_wait(fa, fb, 8);
        flag_wait(fa + 32, fb + 32, 8);
        if (elect_one()) {
          mbar_expect(bar + 8 * B_QG, 20480 + 640);
          bulk_g2s(sb + OFF_G, g_gate + ga * 8, 640, bar + 8 * B_QG);
          mbar_expect(bar + 8 * B_Z, 20480);
        }
#pragma unroll 1
        for (int hf = 0; hf < 2; hf++) {
          if (has1) { mbar_wait_t(bar + 8 * (B_CD + 2 + 2 * hf), 0); mbar_wait_t(bar + 8 * B_Z3, 0); }
          if (elect_one()) { tma4(sb + OFF_Q + hf * 10240, &M.m[mQ], db * 64, 0, ((2 * tb + hf) % 13) * 10, (2 * tb + hf) / 13, bar + 8 * B_QG); TS(110 + hf); }
        }
        flag_wait(&g_cnt[(C_Z + db) * 32], &g_cnt[(C_Z + db) * 32], (64 * db + 63) / 5 - (64 * db) / 5 + 1);
        if (lane == 0) TS(109);
        mbar_wait_t(bar + 8 * B_ZF, 0);
        if (elect_one()) { tma2(sb + OFF_Z, &M.m[mZ], tb * 160, db * 64, bar + 8 * B_Z); TS(35); }
        if (lane == 0 && atomicAdd(&g_cnt[C_DONE * 32], 1u) == NCTA - 1) {
          for (int i = 0; i < C_COUNT; i++) g_cnt[i * 32] = 0;
        }
      } else {
        if (has1) {
          const int g0 = (mb >> 2) * 130 + (mb & 3) * 32;
          mbar_wait_t(bar + 8 * B_GS, 0);
          if (elect_one()) bulk_s2g(g_gate + (g0 + 2 * ft) * 8, sb + OFF_GS, 64);
#pragma unroll 1
          for (int j = 0; j < 4; j++) {
            const int i = (j >> 1) | ((j & 1) << 1);
            mbar_wait_t(bar + 8 * (B_SIGH + i), 0);
            if (elect_one()) {
              tma3_store(&M.m[mH], sb + i * 8192, 0, 3 * ft, g0 + 8 * i);
              tma3_store(&M.m[mH], sb + G1_STAGE + i * 8192, 0, 3 * ft, g0 + 8 * i + 4);
            }
          }
          asm volatile("cp.async.bulk.commit_group;" ::: "memory");
          asm volatile("cp.async.bulk.wait_group.read 0;" ::: "memory");
          __syncwarp();
          if (lane == 0) { mbar_arrive(bar + 8 * B_HDR); TS(45); }
          asm volatile("cp.async.bulk.wait_group 0;" ::: "memory");
          __syncwarp();
          if (lane == 0) { flag_add(&g_cnt[(C_H + 2 * mb + (ft >> 3)) * 32]); TS(42); }
#pragma unroll 1
          for (int j = 0; j < 5; j++) {
            const int ch = j < 4 ? j ^ 1 : 4;
            __nv_bfloat16* zd = g_zT + (size_t)(5 * cta + ch) * (NGRP * 8);
            mbar_wait_t(bar + 8 * (B_SIGZ + ch), 0);
            if (elect_one()) bulk_s2g(zd, sb + zstage(ch), NGRP * 16);
            if (j == 2) {
              asm volatile("cp.async.bulk.commit_group;" ::: "memory");
              asm volatile("cp.async.bulk.wait_group.read 0;" ::: "memory");
              __syncwarp();
              if (lane < 2) mbar_arrive(bar + 8 * B_Z3);
              if (lane == 0) TS(108);
            }
          }
          asm volatile("cp.async.bulk.commit_group;" ::: "memory");
          asm volatile("cp.async.bulk.wait_group 0;" ::: "memory");
          __syncwarp();
          if (lane == 0) flag_add(&g_cnt[(C_Z + (5 * cta) / 64) * 32]);
          if (lane == 0 && (5 * cta) / 64 != (5 * cta + 4) / 64) flag_add(&g_cnt[(C_Z + (5 * cta + 4) / 64) * 32]);
          if (lane == 0) TS(43);
        }
        mbar_wait_t(bar + 8 * B_QC, 0);
        if (lane == 0) asm volatile("mbarrier.arrive.relaxed.cluster.shared::cluster.b64 _, [%0];" ::"r"(peer_addr(bar + 8 * B_XF)) : "memory");
      }
    }
  }
}

typedef CUresult (*EncFn)(CUtensorMap*, CUtensorMapDataType, cuuint32_t, void*, const cuuint64_t*, const cuuint64_t*,
                          const cuuint32_t*, const cuuint32_t*, CUtensorMapInterleave, CUtensorMapSwizzle,
                          CUtensorMapL2promotion, CUtensorMapFloatOOBfill);

void make_map(EncFn enc, CUtensorMap* m, const void* ptr, int rank, const cuuint64_t* dims, const cuuint64_t* str,
              const cuuint32_t* box, CUtensorMapSwizzle sw) {
  const cuuint32_t es[5] = {1, 1, 1, 1, 1};
  enc(m, CU_TENSOR_MAP_DATA_TYPE_BFLOAT16, rank, const_cast<void*>(ptr), dims, str, box, es, CU_TENSOR_MAP_INTERLEAVE_NONE,
      sw, CU_TENSOR_MAP_L2_PROMOTION_L2_128B, CU_TENSOR_MAP_FLOAT_OOB_FILL_NONE);
}

__global__ void probe_kernel() {}

void cluster_order(unsigned char* perm) {
  constexpr int NP = NCTA / 2;
  for (int c = 0; c < NP; c++) perm[c] = c;
  int n[9] = {0};
  cudaFuncSetAttribute(probe_kernel, cudaFuncAttributeMaxDynamicSharedMemorySize, SMEM_BYTES);
  cudaFuncSetAttribute(probe_kernel, cudaFuncAttributeNonPortableClusterSizeAllowed, 1);
  for (int k = 1; k <= 8; k++) {
    cudaLaunchConfig_t cfg = {};
    cudaLaunchAttribute at;
    at.id = cudaLaunchAttributeClusterDimension;
    at.val.clusterDim.x = 2 * k; at.val.clusterDim.y = 1; at.val.clusterDim.z = 1;
    cfg.gridDim = dim3(16 * k); cfg.blockDim = dim3(384); cfg.dynamicSmemBytes = SMEM_BYTES;
    cfg.attrs = &at; cfg.numAttrs = 1;
    if (cudaOccupancyMaxActiveClusters(&n[k], probe_kernel, &cfg) != cudaSuccess) { cudaGetLastError(); return; }
  }
  int R[9];
  R[7] = n[8]; R[6] = n[7]; R[5] = n[6]; R[4] = n[5]; R[3] = n[4] - n[8];
  R[0] = R[1] = R[2] = n[2] - R[3] - R[5] - R[7];
  R[8] = n[3] - R[2] - R[5];
  int lone = n[1];
  for (int r = 0; r < 9; r++) {
    if (R[r] < 0 || R[r] > 16 || (r && R[r] > R[r - 1])) return;
    lone -= R[r];
  }
  if (lone < 0 || n[1] < NP) return;
  int gpc[NP], rnd[NP];
  for (int c = 0, r = 0, pos = 0; c < NP; c++) {
    if (c < lone) { gpc[c] = -1; rnd[c] = 8; continue; }
    while (pos >= R[r]) { pos = 0; r++; }
    gpc[c] = R[0] - R[r] + pos++; rnd[c] = r;
  }
  int m = 0;
  for (int g = R[0] - 1; g >= 0; g--)
    for (int c = 0; c < NP; c++) if (gpc[c] == g && rnd[c] < 8) perm[c] = m++;
  for (int c = NP - 1; c >= 0; c--) if (rnd[c] == 8) perm[c] = m++;
}

}

extern "C" void kernel_launch(void* const* d_in, const int* in_sizes, int n_in, void* d_out, int out_size) {
  (void)in_sizes; (void)n_in; (void)out_size;
  static EncFn enc = nullptr;
  static unsigned char perm[NCTA / 2];
  static void *zT = nullptr, *uT = nullptr, *hT = nullptr;
  if (!enc) {
    cudaDriverEntryPointQueryResult qr;
    cudaGetDriverEntryPoint("cuTensorMapEncodeTiled", (void**)&enc, cudaEnableDefault, &qr);
    cudaGetSymbolAddress(&zT, g_zT);
    cudaGetSymbolAddress(&uT, g_U);
    cudaGetSymbolAddress(&hT, g_Hs);
    cudaFuncSetAttribute(fused_kernel, cudaFuncAttributeMaxDynamicSharedMemorySize, SMEM_BYTES);
    cluster_order(perm);
  }
  Maps M;
  {
    const cuuint64_t dims[4] = {640, 8, 128, 2}, str[3] = {128 * 1280, 1280, 1024 * 1280};
    const cuuint32_t b1[4] = {64, 8, 32, 1}, b2[4] = {64, 8, 10, 1};
    make_map(enc, &M.m[mX], d_in[0], 4, dims, str, b1, CU_TENSOR_MAP_SWIZZLE_128B);
    make_map(enc, &M.m[mQ], d_in[0], 4, dims, str, b2, CU_TENSOR_MAP_SWIZZLE_128B);
    make_map(enc, &M.m[mO], d_out, 4, dims, str, b2, CU_TENSOR_MAP_SWIZZLE_128B);
  }
  {
    const cuuint64_t dims[3] = {32, 640, 48}, str[2] = {3072, 64};
    const cuuint32_t box[3] = {32, 64, 3};
    make_map(enc, &M.m[mWg], d_in[7], 3, dims, str, box, CU_TENSOR_MAP_SWIZZLE_64B);
    make_map(enc, &M.m[mWu], d_in[8], 3, dims, str, box, CU_TENSOR_MAP_SWIZZLE_64B);
  }
  {
    const cuuint64_t dims[3] = {64, 1536, 10}, str[2] = {1280, 128};
    const cuuint32_t box[3] = {64, 64, 1};
    make_map(enc, &M.m[mWd], d_in[9], 3, dims, str, box, CU_TENSOR_MAP_SWIZZLE_128B);
  }
  {
    const cuuint64_t dims[2] = {NGRP * 8, 640}, str[1] = {NGRP * 16};
    const cuuint32_t box[2] = {160, 64};
    make_map(enc, &M.m[mZ], zT, 2, dims, str, box, CU_TENSOR_MAP_SWIZZLE_NONE);
  }
  {
    const cuuint64_t dims[3] = {256, 48, NGRP}, str[2] = {NGRP * 512, 512};
    const cuuint32_t box[3] = {256, 3, 4};
    make_map(enc, &M.m[mH], hT, 3, dims, str, box, CU_TENSOR_MAP_SWIZZLE_NONE);
  }
  {
    const cuuint64_t dims[3] = {640, 256, 8}, str[2] = {8 * 1280, 1280};
    const cuuint32_t bk[3] = {80, 18, 8}, bv[3] = {80, 17, 8};
    make_map(enc, &M.m[mK], d_in[1], 3, dims, str, bk, CU_TENSOR_MAP_SWIZZLE_NONE);
    make_map(enc, &M.m[mV], d_in[2], 3, dims, str, bv, CU_TENSOR_MAP_SWIZZLE_NONE);
  }
  {
    const cuuint64_t dims[2] = {2048, 1280}, str[1] = {4096};
    const cuuint32_t box[2] = {128, 32};
    make_map(enc, &M.m[mU], uT, 2, dims, str, box, CU_TENSOR_MAP_SWIZZLE_NONE);
  }
  Params P;
  P.q = (const __nv_bfloat16*)d_in[0]; P.k = (const __nv_bfloat16*)d_in[1]; P.v = (const __nv_bfloat16*)d_in[2];
  P.w_gate = (const __nv_bfloat16*)d_in[7]; P.w_up = (const __nv_bfloat16*)d_in[8]; P.w_down = (const __nv_bfloat16*)d_in[9];
  P.shift_k = (const __nv_bfloat16*)d_in[3]; P.ssm_k = (const __nv_bfloat16*)d_in[4]; P.ssm_D = (const __nv_bfloat16*)d_in[5];
  P.gate_w = (const __nv_bfloat16*)d_in[10];
  for (int c = 0; c < NCTA / 2; c++) {
    const int p2 = perm[c];
    P.c2[c] = (p2 & 64) + (((p2 >> 1) & 4) | (p2 & 3)) * 8 + (((p2 >> 3) & 6) | ((p2 >> 2) & 1));
    P.g2[c] = (p2 / 5) << 3 | (p2 % 5);
  }
  fused_kernel<<<NCTA, 384, SMEM_BYTES>>>(P, M);
}
```

```cpp
#include <cuda_runtime.h>
#include <cuda.h>
#include <cuda_bf16.h>
#include <stdint.h>

namespace {
#define ZN 0
#define AVS 10
#define CDE 3
#define C4R 0
#define G2W 0
#define QE 1
#define WE 1

#define ODK 12
#define ODS 4
#define ODW 9
#define TM8 0
#define TM9 1
#define TM10 1
#define GMAP 1
#define G1MAP 1
#define REL 2
#define TLA 2
#define CV0 4
#define CA0 65
#define PMW 4
#define PWT 0
#define D1 0
#define D2 0
#define S2W 0
#define TOPO 1
#define HI 0
#define W0W 0
#define CAS 1
#define PKM 1
#define TW 0
#define TOUCH(p) asm volatile("prefetch.global.L2 [%0];" ::"l"(p) : "memory")
#define GWB 0
#define WU 0
#define VW 0
#define DM 0
#define DM0 0
#define DMC 0
#define DME 0
#define PRX 2
#define PRW 2
#define PRD 2
#define PRK 3
#define PRH 2
#define CPF 0
#define CPA "cp.async.cg.shared.global "
#define NSP 0
#define H1A 2
#define H1D 4
#define NAV 10
#define AV1 0
#define P1F 0
#define FW 1
#define FC 3
#define FZ 0
#define DMK 0
#define DMZ 2
static_assert((FZ & 1) == ((FZ >> 1) & 1), "");
#define W2S 0
static_assert(!W2S || FW != 2, "");
#define FK 1
#define UW 1
#define DMN 192
#define DMD 0
#define WH 0
#define WKO(kk) (WH ? ((kk) & 1) * 64 + ((kk) >> 1) * 768 : 64 * (kk))
#define SWP 0
#define NOKV 0
#define CV04 3
#define CV02 5
#define HX(X, i) (((X) >> (4 * (6 - (i)))) & 15)
#define HS1(X) HX(X, 0)
#define HS2(X) HS1(X) + HX(X, 1)
#define HS3(X) HS2(X) + HX(X, 2)
#define HS4(X) HS3(X) + HX(X, 3)
#define HS5(X) HS4(X) + HX(X, 4)
#define HS6(X) HS5(X) + HX(X, 5)
#define HS7(X) HS6(X) + HX(X, 6)
#define CV1X 0x2222222
#define CV1 0, HS1(CV1X), HS2(CV1X), HS3(CV1X), HS4(CV1X), HS5(CV1X), HS6(CV1X), HS7(CV1X)
#define CV4S 0
#define CV4 0, 4, 8, 12, 16, 22, 26, 29
#define GL1S 1
#define GL1 0, 1, 3, 4, 6, 7, 9
#define G1SB sb
#define KVAT 0
#define KVPF 2
#define KVA 0
#define KVB 2
#define REL2 3
#define PFS 0
#define PFKV 0
#define PFM 0
#define PFL(p) asm volatile("prefetch.global.L2 [%0];" ::"l"(p) : "memory")
#define PFS3 0
#define PF0 3
#define PFD 0
#define PFD2 0
#define VAT 3
#define FCP 0
#define S0M 0
#define VPF 0
#define TAIL 1
#define KVX 0
#define KVXM 0
#define KVX_AT(i) do { if ((KVX >> (i)) & 1) __syncwarp(); } while (0)
#define SPN 1
#define SPD 1
#define AVL 0
#define P1E 0
#define KVTS 2
#define KVLD 0
#define KVW 1
#define C4ALL 0
#define PFK 5
#define PFW 7

template<int TA, int TB> __device__ __forceinline__ void wgmma_n8(float* d, uint64_t da, uint64_t db, int sc) {
  asm volatile("{\n.reg .pred p;\nsetp.ne.b32 p, %6, 0;\n"
    "wgmma.mma_async.sync.aligned.m64n8k16.f32.bf16.bf16 {%0, %1, %2, %3}, %4, %5, p, 1, 1, %7, %8;\n}\n"
    : "+f"(d[0]), "+f"(d[1]), "+f"(d[2]), "+f"(d[3])
    : "l"(da), "l"(db), "r"(sc), "n"(TA), "n"(TB));
}
template<int TA, int TB> __device__ __forceinline__ void wgmma_n16(float* d, uint64_t da, uint64_t db, int sc) {
  asm volatile("{\n.reg .pred p;\nsetp.ne.b32 p, %10, 0;\n"
    "wgmma.mma_async.sync.aligned.m64n16k16.f32.bf16.bf16 {%0, %1, %2, %3, %4, %5, %6, %7}, %8, %9, p, 1, 1, %11, %12;\n}\n"
    : "+f"(d[0]), "+f"(d[1]), "+f"(d[2]), "+f"(d[3]), "+f"(d[4]), "+f"(d[5]), "+f"(d[6]), "+f"(d[7])
    : "l"(da), "l"(db), "r"(sc), "n"(TA), "n"(TB));
}
template<int TA, int TB> __device__ __forceinline__ void wgmma_n24(float* d, uint64_t da, uint64_t db, int sc) {
  asm volatile("{\n.reg .pred p;\nsetp.ne.b32 p, %14, 0;\n"
    "wgmma.mma_async.sync.aligned.m64n24k16.f32.bf16.bf16 {%0, %1, %2, %3, %4, %5, %6, %7, %8, %9, %10, %11}, %12, %13, p, 1, 1, %15, %16;\n}\n"
    : "+f"(d[0]), "+f"(d[1]), "+f"(d[2]), "+f"(d[3]), "+f"(d[4]), "+f"(d[5]), "+f"(d[6]), "+f"(d[7]), "+f"(d[8]), "+f"(d[9]), "+f"(d[10]), "+f"(d[11])
    : "l"(da), "l"(db), "r"(sc), "n"(TA), "n"(TB));
}
template<int TA, int TB> __device__ __forceinline__ void wgmma_n32(float* d, uint64_t da, uint64_t db, int sc) {
  asm volatile("{\n.reg .pred p;\nsetp.ne.b32 p, %18, 0;\n"
    "wgmma.mma_async.sync.aligned.m64n32k16.f32.bf16.bf16 {%0, %1, %2, %3, %4, %5, %6, %7, %8, %9, %10, %11, %12, %13, %14, %15}, %16, %17, p, 1, 1, %19, %20;\n}\n"
    : "+f"(d[0]), "+f"(d[1]), "+f"(d[2]), "+f"(d[3]), "+f"(d[4]), "+f"(d[5]), "+f"(d[6]), "+f"(d[7]), "+f"(d[8]), "+f"(d[9]), "+f"(d[10]), "+f"(d[11]), "+f"(d[12]), "+f"(d[13]), "+f"(d[14]), "+f"(d[15])
    : "l"(da), "l"(db), "r"(sc), "n"(TA), "n"(TB));
}
template<int TA, int TB> __device__ __forceinline__ void wgmma_n40(float* d, uint64_t da, uint64_t db, int sc) {
  asm volatile("{\n.reg .pred p;\nsetp.ne.b32 p, %22, 0;\n"
    "wgmma.mma_async.sync.aligned.m64n40k16.f32.bf16.bf16 {%0, %1, %2, %3, %4, %5, %6, %7, %8, %9, %10, %11, %12, %13, %14, %15, %16, %17, %18, %19}, %20, %21, p, 1, 1, %23, %24;\n}\n"
    : "+f"(d[0]), "+f"(d[1]), "+f"(d[2]), "+f"(d[3]), "+f"(d[4]), "+f"(d[5]), "+f"(d[6]), "+f"(d[7]), "+f"(d[8]), "+f"(d[9]), "+f"(d[10]), "+f"(d[11]), "+f"(d[12]), "+f"(d[13]), "+f"(d[14]), "+f"(d[15]), "+f"(d[16]), "+f"(d[17]), "+f"(d[18]), "+f"(d[19])
    : "l"(da), "l"(db), "r"(sc), "n"(TA), "n"(TB));
}
template<int TA, int TB> __device__ __forceinline__ void wgmma_n48(float* d, uint64_t da, uint64_t db, int sc) {
  asm volatile("{\n.reg .pred p;\nsetp.ne.b32 p, %26, 0;\n"
    "wgmma.mma_async.sync.aligned.m64n48k16.f32.bf16.bf16 {%0, %1, %2, %3, %4, %5, %6, %7, %8, %9, %10, %11, %12, %13, %14, %15, %16, %17, %18, %19, %20, %21, %22, %23}, %24, %25, p, 1, 1, %27, %28;\n}\n"
    : "+f"(d[0]), "+f"(d[1]), "+f"(d[2]), "+f"(d[3]), "+f"(d[4]), "+f"(d[5]), "+f"(d[6]), "+f"(d[7]), "+f"(d[8]), "+f"(d[9]), "+f"(d[10]), "+f"(d[11]), "+f"(d[12]), "+f"(d[13]), "+f"(d[14]), "+f"(d[15]), "+f"(d[16]), "+f"(d[17]), "+f"(d[18]), "+f"(d[19]), "+f"(d[20]), "+f"(d[21]), "+f"(d[22]), "+f"(d[23])
    : "l"(da), "l"(db), "r"(sc), "n"(TA), "n"(TB));
}
template<int TA, int TB> __device__ __forceinline__ void wgmma_n56(float* d, uint64_t da, uint64_t db, int sc) {
  asm volatile("{\n.reg .pred p;\nsetp.ne.b32 p, %30, 0;\n"
    "wgmma.mma_async.sync.aligned.m64n56k16.f32.bf16.bf16 {%0, %1, %2, %3, %4, %5, %6, %7, %8, %9, %10, %11, %12, %13, %14, %15, %16, %17, %18, %19, %20, %21, %22, %23, %24, %25, %26, %27}, %28, %29, p, 1, 1, %31, %32;\n}\n"
    : "+f"(d[0]), "+f"(d[1]), "+f"(d[2]), "+f"(d[3]), "+f"(d[4]), "+f"(d[5]), "+f"(d[6]), "+f"(d[7]), "+f"(d[8]), "+f"(d[9]), "+f"(d[10]), "+f"(d[11]), "+f"(d[12]), "+f"(d[13]), "+f"(d[14]), "+f"(d[15]), "+f"(d[16]), "+f"(d[17]), "+f"(d[18]), "+f"(d[19]), "+f"(d[20]), "+f"(d[21]), "+f"(d[22]), "+f"(d[23]), "+f"(d[24]), "+f"(d[25]), "+f"(d[26]), "+f"(d[27])
    : "l"(da), "l"(db), "r"(sc), "n"(TA), "n"(TB));
}
template<int TA, int TB> __device__ __forceinline__ void wgmma_n64(float* d, uint64_t da, uint64_t db, int sc) {
  asm volatile("{\n.reg .pred p;\nsetp.ne.b32 p, %34, 0;\n"
    "wgmma.mma_async.sync.aligned.m64n64k16.f32.bf16.bf16 {%0, %1, %2, %3, %4, %5, %6, %7, %8, %9, %10, %11, %12, %13, %14, %15, %16, %17, %18, %19, %20, %21, %22, %23, %24, %25, %26, %27, %28, %29, %30, %31}, %32, %33, p, 1, 1, %35, %36;\n}\n"
    : "+f"(d[0]), "+f"(d[1]), "+f"(d[2]), "+f"(d[3]), "+f"(d[4]), "+f"(d[5]), "+f"(d[6]), "+f"(d[7]), "+f"(d[8]), "+f"(d[9]), "+f"(d[10]), "+f"(d[11]), "+f"(d[12]), "+f"(d[13]), "+f"(d[14]), "+f"(d[15]), "+f"(d[16]), "+f"(d[17]), "+f"(d[18]), "+f"(d[19]), "+f"(d[20]), "+f"(d[21]), "+f"(d[22]), "+f"(d[23]), "+f"(d[24]), "+f"(d[25]), "+f"(d[26]), "+f"(d[27]), "+f"(d[28]), "+f"(d[29]), "+f"(d[30]), "+f"(d[31])
    : "l"(da), "l"(db), "r"(sc), "n"(TA), "n"(TB));
}
template<int TA, int TB> __device__ __forceinline__ void wgmma_n72(float* d, uint64_t da, uint64_t db, int sc) {
  asm volatile("{\n.reg .pred p;\nsetp.ne.b32 p, %38, 0;\n"
    "wgmma.mma_async.sync.aligned.m64n72k16.f32.bf16.bf16 {%0, %1, %2, %3, %4, %5, %6, %7, %8, %9, %10, %11, %12, %13, %14, %15, %16, %17, %18, %19, %20, %21, %22, %23, %24, %25, %26, %27, %28, %29, %30, %31, %32, %33, %34, %35}, %36, %37, p, 1, 1, %39, %40;\n}\n"
    : "+f"(d[0]), "+f"(d[1]), "+f"(d[2]), "+f"(d[3]), "+f"(d[4]), "+f"(d[5]), "+f"(d[6]), "+f"(d[7]), "+f"(d[8]), "+f"(d[9]), "+f"(d[10]), "+f"(d[11]), "+f"(d[12]), "+f"(d[13]), "+f"(d[14]), "+f"(d[15]), "+f"(d[16]), "+f"(d[17]), "+f"(d[18]), "+f"(d[19]), "+f"(d[20]), "+f"(d[21]), "+f"(d[22]), "+f"(d[23]), "+f"(d[24]), "+f"(d[25]), "+f"(d[26]), "+f"(d[27]), "+f"(d[28]), "+f"(d[29]), "+f"(d[30]), "+f"(d[31]), "+f"(d[32]), "+f"(d[33]), "+f"(d[34]), "+f"(d[35])
    : "l"(da), "l"(db), "r"(sc), "n"(TA), "n"(TB));
}
template<int TA, int TB> __device__ __forceinline__ void wgmma_n80(float* d, uint64_t da, uint64_t db, int sc) {
  asm volatile("{\n.reg .pred p;\nsetp.ne.b32 p, %42, 0;\n"
    "wgmma.mma_async.sync.aligned.m64n80k16.f32.bf16.bf16 {%0, %1, %2, %3, %4, %5, %6, %7, %8, %9, %10, %11, %12, %13, %14, %15, %16, %17, %18, %19, %20, %21, %22, %23, %24, %25, %26, %27, %28, %29, %30, %31, %32, %33, %34, %35, %36, %37, %38, %39}, %40, %41, p, 1, 1, %43, %44;\n}\n"
    : "+f"(d[0]), "+f"(d[1]), "+f"(d[2]), "+f"(d[3]), "+f"(d[4]), "+f"(d[5]), "+f"(d[6]), "+f"(d[7]), "+f"(d[8]), "+f"(d[9]), "+f"(d[10]), "+f"(d[11]), "+f"(d[12]), "+f"(d[13]), "+f"(d[14]), "+f"(d[15]), "+f"(d[16]), "+f"(d[17]), "+f"(d[18]), "+f"(d[19]), "+f"(d[20]), "+f"(d[21]), "+f"(d[22]), "+f"(d[23]), "+f"(d[24]), "+f"(d[25]), "+f"(d[26]), "+f"(d[27]), "+f"(d[28]), "+f"(d[29]), "+f"(d[30]), "+f"(d[31]), "+f"(d[32]), "+f"(d[33]), "+f"(d[34]), "+f"(d[35]), "+f"(d[36]), "+f"(d[37]), "+f"(d[38]), "+f"(d[39])
    : "l"(da), "l"(db), "r"(sc), "n"(TA), "n"(TB));
}
template<int TA, int TB> __device__ __forceinline__ void wgmma_n88(float* d, uint64_t da, uint64_t db, int sc) {
  asm volatile("{\n.reg .pred p;\nsetp.ne.b32 p, %46, 0;\n"
    "wgmma.mma_async.sync.aligned.m64n88k16.f32.bf16.bf16 {%0, %1, %2, %3, %4, %5, %6, %7, %8, %9, %10, %11, %12, %13, %14, %15, %16, %17, %18, %19, %20, %21, %22, %23, %24, %25, %26, %27, %28, %29, %30, %31, %32, %33, %34, %35, %36, %37, %38, %39, %40, %41, %42, %43}, %44, %45, p, 1, 1, %47, %48;\n}\n"
    : "+f"(d[0]), "+f"(d[1]), "+f"(d[2]), "+f"(d[3]), "+f"(d[4]), "+f"(d[5]), "+f"(d[6]), "+f"(d[7]), "+f"(d[8]), "+f"(d[9]), "+f"(d[10]), "+f"(d[11]), "+f"(d[12]), "+f"(d[13]), "+f"(d[14]), "+f"(d[15]), "+f"(d[16]), "+f"(d[17]), "+f"(d[18]), "+f"(d[19]), "+f"(d[20]), "+f"(d[21]), "+f"(d[22]), "+f"(d[23]), "+f"(d[24]), "+f"(d[25]), "+f"(d[26]), "+f"(d[27]), "+f"(d[28]), "+f"(d[29]), "+f"(d[30]), "+f"(d[31]), "+f"(d[32]), "+f"(d[33]), "+f"(d[34]), "+f"(d[35]), "+f"(d[36]), "+f"(d[37]), "+f"(d[38]), "+f"(d[39]), "+f"(d[40]), "+f"(d[41]), "+f"(d[42]), "+f"(d[43])
    : "l"(da), "l"(db), "r"(sc), "n"(TA), "n"(TB));
}
template<int TA, int TB> __device__ __forceinline__ void wgmma_n96(float* d, uint64_t da, uint64_t db, int sc) {
  asm volatile("{\n.reg .pred p;\nsetp.ne.b32 p, %50, 0;\n"
    "wgmma.mma_async.sync.aligned.m64n96k16.f32.bf16.bf16 {%0, %1, %2, %3, %4, %5, %6, %7, %8, %9, %10, %11, %12, %13, %14, %15, %16, %17, %18, %19, %20, %21, %22, %23, %24, %25, %26, %27, %28, %29, %30, %31, %32, %33, %34, %35, %36, %37, %38, %39, %40, %41, %42, %43, %44, %45, %46, %47}, %48, %49, p, 1, 1, %51, %52;\n}\n"
    : "+f"(d[0]), "+f"(d[1]), "+f"(d[2]), "+f"(d[3]), "+f"(d[4]), "+f"(d[5]), "+f"(d[6]), "+f"(d[7]), "+f"(d[8]), "+f"(d[9]), "+f"(d[10]), "+f"(d[11]), "+f"(d[12]), "+f"(d[13]), "+f"(d[14]), "+f"(d[15]), "+f"(d[16]), "+f"(d[17]), "+f"(d[18]), "+f"(d[19]), "+f"(d[20]), "+f"(d[21]), "+f"(d[22]), "+f"(d[23]), "+f"(d[24]), "+f"(d[25]), "+f"(d[26]), "+f"(d[27]), "+f"(d[28]), "+f"(d[29]), "+f"(d[30]), "+f"(d[31]), "+f"(d[32]), "+f"(d[33]), "+f"(d[34]), "+f"(d[35]), "+f"(d[36]), "+f"(d[37]), "+f"(d[38]), "+f"(d[39]), "+f"(d[40]), "+f"(d[41]), "+f"(d[42]), "+f"(d[43]), "+f"(d[44]), "+f"(d[45]), "+f"(d[46]), "+f"(d[47])
    : "l"(da), "l"(db), "r"(sc), "n"(TA), "n"(TB));
}
template<int TA, int TB> __device__ __forceinline__ void wgmma_n104(float* d, uint64_t da, uint64_t db, int sc) {
  asm volatile("{\n.reg .pred p;\nsetp.ne.b32 p, %54, 0;\n"
    "wgmma.mma_async.sync.aligned.m64n104k16.f32.bf16.bf16 {%0, %1, %2, %3, %4, %5, %6, %7, %8, %9, %10, %11, %12, %13, %14, %15, %16, %17, %18, %19, %20, %21, %22, %23, %24, %25, %26, %27, %28, %29, %30, %31, %32, %33, %34, %35, %36, %37, %38, %39, %40, %41, %42, %43, %44, %45, %46, %47, %48, %49, %50, %51}, %52, %53, p, 1, 1, %55, %56;\n}\n"
    : "+f"(d[0]), "+f"(d[1]), "+f"(d[2]), "+f"(d[3]), "+f"(d[4]), "+f"(d[5]), "+f"(d[6]), "+f"(d[7]), "+f"(d[8]), "+f"(d[9]), "+f"(d[10]), "+f"(d[11]), "+f"(d[12]), "+f"(d[13]), "+f"(d[14]), "+f"(d[15]), "+f"(d[16]), "+f"(d[17]), "+f"(d[18]), "+f"(d[19]), "+f"(d[20]), "+f"(d[21]), "+f"(d[22]), "+f"(d[23]), "+f"(d[24]), "+f"(d[25]), "+f"(d[26]), "+f"(d[27]), "+f"(d[28]), "+f"(d[29]), "+f"(d[30]), "+f"(d[31]), "+f"(d[32]), "+f"(d[33]), "+f"(d[34]), "+f"(d[35]), "+f"(d[36]), "+f"(d[37]), "+f"(d[38]), "+f"(d[39]), "+f"(d[40]), "+f"(d[41]), "+f"(d[42]), "+f"(d[43]), "+f"(d[44]), "+f"(d[45]), "+f"(d[46]), "+f"(d[47]), "+f"(d[48]), "+f"(d[49]), "+f"(d[50]), "+f"(d[51])
    : "l"(da), "l"(db), "r"(sc), "n"(TA), "n"(TB));
}
template<int TA, int TB> __device__ __forceinline__ void wgmma_n112(float* d, uint64_t da, uint64_t db, int sc) {
  asm volatile("{\n.reg .pred p;\nsetp.ne.b32 p, %58, 0;\n"
    "wgmma.mma_async.sync.aligned.m64n112k16.f32.bf16.bf16 {%0, %1, %2, %3, %4, %5, %6, %7, %8, %9, %10, %11, %12, %13, %14, %15, %16, %17, %18, %19, %20, %21, %22, %23, %24, %25, %26, %27, %28, %29, %30, %31, %32, %33, %34, %35, %36, %37, %38, %39, %40, %41, %42, %43, %44, %45, %46, %47, %48, %49, %50, %51, %52, %53, %54, %55}, %56, %57, p, 1, 1, %59, %60;\n}\n"
    : "+f"(d[0]), "+f"(d[1]), "+f"(d[2]), "+f"(d[3]), "+f"(d[4]), "+f"(d[5]), "+f"(d[6]), "+f"(d[7]), "+f"(d[8]), "+f"(d[9]), "+f"(d[10]), "+f"(d[11]), "+f"(d[12]), "+f"(d[13]), "+f"(d[14]), "+f"(d[15]), "+f"(d[16]), "+f"(d[17]), "+f"(d[18]), "+f"(d[19]), "+f"(d[20]), "+f"(d[21]), "+f"(d[22]), "+f"(d[23]), "+f"(d[24]), "+f"(d[25]), "+f"(d[26]), "+f"(d[27]), "+f"(d[28]), "+f"(d[29]), "+f"(d[30]), "+f"(d[31]), "+f"(d[32]), "+f"(d[33]), "+f"(d[34]), "+f"(d[35]), "+f"(d[36]), "+f"(d[37]), "+f"(d[38]), "+f"(d[39]), "+f"(d[40]), "+f"(d[41]), "+f"(d[42]), "+f"(d[43]), "+f"(d[44]), "+f"(d[45]), "+f"(d[46]), "+f"(d[47]), "+f"(d[48]), "+f"(d[49]), "+f"(d[50]), "+f"(d[51]), "+f"(d[52]), "+f"(d[53]), "+f"(d[54]), "+f"(d[55])
    : "l"(da), "l"(db), "r"(sc), "n"(TA), "n"(TB));
}
template<int TA, int TB> __device__ __forceinline__ void wgmma_n120(float* d, uint64_t da, uint64_t db, int sc) {
  asm volatile("{\n.reg .pred p;\nsetp.ne.b32 p, %62, 0;\n"
    "wgmma.mma_async.sync.aligned.m64n120k16.f32.bf16.bf16 {%0, %1, %2, %3, %4, %5, %6, %7, %8, %9, %10, %11, %12, %13, %14, %15, %16, %17, %18, %19, %20, %21, %22, %23, %24, %25, %26, %27, %28, %29, %30, %31, %32, %33, %34, %35, %36, %37, %38, %39, %40, %41, %42, %43, %44, %45, %46, %47, %48, %49, %50, %51, %52, %53, %54, %55, %56, %57, %58, %59}, %60, %61, p, 1, 1, %63, %64;\n}\n"
    : "+f"(d[0]), "+f"(d[1]), "+f"(d[2]), "+f"(d[3]), "+f"(d[4]), "+f"(d[5]), "+f"(d[6]), "+f"(d[7]), "+f"(d[8]), "+f"(d[9]), "+f"(d[10]), "+f"(d[11]), "+f"(d[12]), "+f"(d[13]), "+f"(d[14]), "+f"(d[15]), "+f"(d[16]), "+f"(d[17]), "+f"(d[18]), "+f"(d[19]), "+f"(d[20]), "+f"(d[21]), "+f"(d[22]), "+f"(d[23]), "+f"(d[24]), "+f"(d[25]), "+f"(d[26]), "+f"(d[27]), "+f"(d[28]), "+f"(d[29]), "+f"(d[30]), "+f"(d[31]), "+f"(d[32]), "+f"(d[33]), "+f"(d[34]), "+f"(d[35]), "+f"(d[36]), "+f"(d[37]), "+f"(d[38]), "+f"(d[39]), "+f"(d[40]), "+f"(d[41]), "+f"(d[42]), "+f"(d[43]), "+f"(d[44]), "+f"(d[45]), "+f"(d[46]), "+f"(d[47]), "+f"(d[48]), "+f"(d[49]), "+f"(d[50]), "+f"(d[51]), "+f"(d[52]), "+f"(d[53]), "+f"(d[54]), "+f"(d[55]), "+f"(d[56]), "+f"(d[57]), "+f"(d[58]), "+f"(d[59])
    : "l"(da), "l"(db), "r"(sc), "n"(TA), "n"(TB));
}
template<int TA, int TB> __device__ __forceinline__ void wgmma_n128(float* d, uint64_t da, uint64_t db, int sc) {
  asm volatile("{\n.reg .pred p;\nsetp.ne.b32 p, %66, 0;\n"
    "wgmma.mma_async.sync.aligned.m64n128k16.f32.bf16.bf16 {%0, %1, %2, %3, %4, %5, %6, %7, %8, %9, %10, %11, %12, %13, %14, %15, %16, %17, %18, %19, %20, %21, %22, %23, %24, %25, %26, %27, %28, %29, %30, %31, %32, %33, %34, %35, %36, %37, %38, %39, %40, %41, %42, %43, %44, %45, %46, %47, %48, %49, %50, %51, %52, %53, %54, %55, %56, %57, %58, %59, %60, %61, %62, %63}, %64, %65, p, 1, 1, %67, %68;\n}\n"
    : "+f"(d[0]), "+f"(d[1]), "+f"(d[2]), "+f"(d[3]), "+f"(d[4]), "+f"(d[5]), "+f"(d[6]), "+f"(d[7]), "+f"(d[8]), "+f"(d[9]), "+f"(d[10]), "+f"(d[11]), "+f"(d[12]), "+f"(d[13]), "+f"(d[14]), "+f"(d[15]), "+f"(d[16]), "+f"(d[17]), "+f"(d[18]), "+f"(d[19]), "+f"(d[20]), "+f"(d[21]), "+f"(d[22]), "+f"(d[23]), "+f"(d[24]), "+f"(d[25]), "+f"(d[26]), "+f"(d[27]), "+f"(d[28]), "+f"(d[29]), "+f"(d[30]), "+f"(d[31]), "+f"(d[32]), "+f"(d[33]), "+f"(d[34]), "+f"(d[35]), "+f"(d[36]), "+f"(d[37]), "+f"(d[38]), "+f"(d[39]), "+f"(d[40]), "+f"(d[41]), "+f"(d[42]), "+f"(d[43]), "+f"(d[44]), "+f"(d[45]), "+f"(d[46]), "+f"(d[47]), "+f"(d[48]), "+f"(d[49]), "+f"(d[50]), "+f"(d[51]), "+f"(d[52]), "+f"(d[53]), "+f"(d[54]), "+f"(d[55]), "+f"(d[56]), "+f"(d[57]), "+f"(d[58]), "+f"(d[59]), "+f"(d[60]), "+f"(d[61]), "+f"(d[62]), "+f"(d[63])
    : "l"(da), "l"(db), "r"(sc), "n"(TA), "n"(TB));
}
template<int TA, int TB> __device__ __forceinline__ void wgmma_n160(float* d, uint64_t da, uint64_t db, int sc) {
  asm volatile("{\n.reg .pred p;\nsetp.ne.b32 p, %82, 0;\n"
    "wgmma.mma_async.sync.aligned.m64n160k16.f32.bf16.bf16 {%0, %1, %2, %3, %4, %5, %6, %7, %8, %9, %10, %11, %12, %13, %14, %15, %16, %17, %18, %19, %20, %21, %22, %23, %24, %25, %26, %27, %28, %29, %30, %31, %32, %33, %34, %35, %36, %37, %38, %39, %40, %41, %42, %43, %44, %45, %46, %47, %48, %49, %50, %51, %52, %53, %54, %55, %56, %57, %58, %59, %60, %61, %62, %63, %64, %65, %66, %67, %68, %69, %70, %71, %72, %73, %74, %75, %76, %77, %78, %79}, %80, %81, p, 1, 1, %83, %84;\n}\n"
    : "+f"(d[0]), "+f"(d[1]), "+f"(d[2]), "+f"(d[3]), "+f"(d[4]), "+f"(d[5]), "+f"(d[6]), "+f"(d[7]), "+f"(d[8]), "+f"(d[9]), "+f"(d[10]), "+f"(d[11]), "+f"(d[12]), "+f"(d[13]), "+f"(d[14]), "+f"(d[15]), "+f"(d[16]), "+f"(d[17]), "+f"(d[18]), "+f"(d[19]), "+f"(d[20]), "+f"(d[21]), "+f"(d[22]), "+f"(d[23]), "+f"(d[24]), "+f"(d[25]), "+f"(d[26]), "+f"(d[27]), "+f"(d[28]), "+f"(d[29]), "+f"(d[30]), "+f"(d[31]), "+f"(d[32]), "+f"(d[33]), "+f"(d[34]), "+f"(d[35]), "+f"(d[36]), "+f"(d[37]), "+f"(d[38]), "+f"(d[39]), "+f"(d[40]), "+f"(d[41]), "+f"(d[42]), "+f"(d[43]), "+f"(d[44]), "+f"(d[45]), "+f"(d[46]), "+f"(d[47]), "+f"(d[48]), "+f"(d[49]), "+f"(d[50]), "+f"(d[51]), "+f"(d[52]), "+f"(d[53]), "+f"(d[54]), "+f"(d[55]), "+f"(d[56]), "+f"(d[57]), "+f"(d[58]), "+f"(d[59]), "+f"(d[60]), "+f"(d[61]), "+f"(d[62]), "+f"(d[63]), "+f"(d[64]), "+f"(d[65]), "+f"(d[66]), "+f"(d[67]), "+f"(d[68]), "+f"(d[69]), "+f"(d[70]), "+f"(d[71]), "+f"(d[72]), "+f"(d[73]), "+f"(d[74]), "+f"(d[75]), "+f"(d[76]), "+f"(d[77]), "+f"(d[78]), "+f"(d[79])
    : "l"(da), "l"(db), "r"(sc), "n"(TA), "n"(TB));
}
template<int TA, int TB> __device__ __forceinline__ void wgmma_n192(float* d, uint64_t da, uint64_t db, int sc) {
  asm volatile("{\n.reg .pred p;\nsetp.ne.b32 p, %98, 0;\n"
    "wgmma.mma_async.sync.aligned.m64n192k16.f32.bf16.bf16 {%0, %1, %2, %3, %4, %5, %6, %7, %8, %9, %10, %11, %12, %13, %14, %15, %16, %17, %18, %19, %20, %21, %22, %23, %24, %25, %26, %27, %28, %29, %30, %31, %32, %33, %34, %35, %36, %37, %38, %39, %40, %41, %42, %43, %44, %45, %46, %47, %48, %49, %50, %51, %52, %53, %54, %55, %56, %57, %58, %59, %60, %61, %62, %63, %64, %65, %66, %67, %68, %69, %70, %71, %72, %73, %74, %75, %76, %77, %78, %79, %80, %81, %82, %83, %84, %85, %86, %87, %88, %89, %90, %91, %92, %93, %94, %95}, %96, %97, p, 1, 1, %99, %100;\n}\n"
    : "+f"(d[0]), "+f"(d[1]), "+f"(d[2]), "+f"(d[3]), "+f"(d[4]), "+f"(d[5]), "+f"(d[6]), "+f"(d[7]), "+f"(d[8]), "+f"(d[9]), "+f"(d[10]), "+f"(d[11]), "+f"(d[12]), "+f"(d[13]), "+f"(d[14]), "+f"(d[15]), "+f"(d[16]), "+f"(d[17]), "+f"(d[18]), "+f"(d[19]), "+f"(d[20]), "+f"(d[21]), "+f"(d[22]), "+f"(d[23]), "+f"(d[24]), "+f"(d[25]), "+f"(d[26]), "+f"(d[27]), "+f"(d[28]), "+f"(d[29]), "+f"(d[30]), "+f"(d[31]), "+f"(d[32]), "+f"(d[33]), "+f"(d[34]), "+f"(d[35]), "+f"(d[36]), "+f"(d[37]), "+f"(d[38]), "+f"(d[39]), "+f"(d[40]), "+f"(d[41]), "+f"(d[42]), "+f"(d[43]), "+f"(d[44]), "+f"(d[45]), "+f"(d[46]), "+f"(d[47]), "+f"(d[48]), "+f"(d[49]), "+f"(d[50]), "+f"(d[51]), "+f"(d[52]), "+f"(d[53]), "+f"(d[54]), "+f"(d[55]), "+f"(d[56]), "+f"(d[57]), "+f"(d[58]), "+f"(d[59]), "+f"(d[60]), "+f"(d[61]), "+f"(d[62]), "+f"(d[63]), "+f"(d[64]), "+f"(d[65]), "+f"(d[66]), "+f"(d[67]), "+f"(d[68]), "+f"(d[69]), "+f"(d[70]), "+f"(d[71]), "+f"(d[72]), "+f"(d[73]), "+f"(d[74]), "+f"(d[75]), "+f"(d[76]), "+f"(d[77]), "+f"(d[78]), "+f"(d[79]), "+f"(d[80]), "+f"(d[81]), "+f"(d[82]), "+f"(d[83]), "+f"(d[84]), "+f"(d[85]), "+f"(d[86]), "+f"(d[87]), "+f"(d[88]), "+f"(d[89]), "+f"(d[90]), "+f"(d[91]), "+f"(d[92]), "+f"(d[93]), "+f"(d[94]), "+f"(d[95])
    : "l"(da), "l"(db), "r"(sc), "n"(TA), "n"(TB));
}
template<int N, int TA, int TB> __device__ __forceinline__ void wgmma_ss(float* d, uint64_t da, uint64_t db, int sc) {
  if constexpr (N == 8) wgmma_n8<TA,TB>(d, da, db, sc);
  if constexpr (N == 16) wgmma_n16<TA,TB>(d, da, db, sc);
  if constexpr (N == 24) wgmma_n24<TA,TB>(d, da, db, sc);
  if constexpr (N == 32) wgmma_n32<TA,TB>(d, da, db, sc);
  if constexpr (N == 40) wgmma_n40<TA,TB>(d, da, db, sc);
  if constexpr (N == 48) wgmma_n48<TA,TB>(d, da, db, sc);
  if constexpr (N == 56) wgmma_n56<TA,TB>(d, da, db, sc);
  if constexpr (N == 64) wgmma_n64<TA,TB>(d, da, db, sc);
  if constexpr (N == 72) wgmma_n72<TA,TB>(d, da, db, sc);
  if constexpr (N == 80) wgmma_n80<TA,TB>(d, da, db, sc);
  if constexpr (N == 88) wgmma_n88<TA,TB>(d, da, db, sc);
  if constexpr (N == 96) wgmma_n96<TA,TB>(d, da, db, sc);
  if constexpr (N == 104) wgmma_n104<TA,TB>(d, da, db, sc);
  if constexpr (N == 112) wgmma_n112<TA,TB>(d, da, db, sc);
  if constexpr (N == 120) wgmma_n120<TA,TB>(d, da, db, sc);
  if constexpr (N == 128) wgmma_n128<TA,TB>(d, da, db, sc);
  if constexpr (N == 160) wgmma_n160<TA,TB>(d, da, db, sc);
  if constexpr (N == 192) wgmma_n192<TA,TB>(d, da, db, sc);
}

constexpr int NGRP = 260;
constexpr uint32_t G1_STAGE = 57344;
constexpr uint32_t OFF_U = 131072;
constexpr uint32_t OFF_H = 172032;
constexpr uint32_t H_PITCH = 4352;
constexpr uint32_t OFF_ZS = 215552;
constexpr uint32_t OFF_EX = OFF_ZS + 12544;
constexpr uint32_t OFF_G = OFF_EX + 2304;
constexpr uint32_t OFF_BAR = OFF_G + 640;
constexpr uint32_t OFF_GS = OFF_BAR + 512;
constexpr uint32_t SMEM_BYTES = OFF_GS + 64 + 512;
constexpr uint32_t OFF_V = OFF_H + 23040;
constexpr uint32_t OFF_US = OFF_ZS + 1536;
constexpr int NCTA = 130;
constexpr uint32_t SB0 = 1024;

enum { B_FULL1 = 0, B_KV = 3,
       B_FULL2 = 4, B_EMPTY2 = 9, B_CD = 14, B_HLD = 19, B_QG = 20, B_GATE = 21, B_GS = 22,
       B_HDR = 23, B_XCH = 24, B_Z = 26, B_XF = 27,
       B_EMPTY1 = 28, B_G1DONE = 31, B_Z3 = 32, B_ZF = 33,
       B_R2FREE = 34, B_UFULL = 35,
       B_SIGH = 40, B_SIGZ = 44, B_QC = 49, B_CE = 50, B_O = 52, B_ZD = 56, B_GO = 57 };
enum { C_H = 0, C_U = 16, C_Z = 24, C_DONE = 34, C_COUNT = 35 };
__host__ __device__ constexpr uint32_t slotF(int s) { return s == 0 ? 114688 : s == 1 ? 32768 : s == 2 ? 90112 : s == 3 ? 49152 : 139264; }
__host__ __device__ constexpr uint32_t slotO(int s) { return s == 3 ? 106496 : slotF(s) + 8192; }
__host__ __device__ constexpr uint32_t slotB0(int s) { return s == 0 ? 0 : s == 1 ? 20480 : s == 2 ? 67584 : s == 3 ? 155648 : 176128; }
__host__ __device__ constexpr uint32_t slotB1(int s) { return s == 1 ? 57344 : slotB0(s) + 10240; }
constexpr int B_C2 = (CDE & 1) ? B_CE : B_CD + 2, B_C4 = (CDE & 2) ? B_CE + 1 : B_CD + 4;
constexpr uint32_t OFF_Q = 196608, OFF_XCH = OFF_Q, OFF_OUT = slotB0(ZN ? 2 : 3);
__device__ __forceinline__ uint32_t zbox(int b) { return !ZN ? slotB0(2) + b * 2560 : b * 2560 + (b < 3 ? OFF_U : OFF_Q + 20480 - 7680); }
__device__ __forceinline__ uint32_t zstage(int ch) { return ch < 3 ? OFF_ZS + ch * 4160 : OFF_U + (4 - ch) * 8192; }

__device__ __align__(1024) __nv_bfloat16 g_Hs[48 * NGRP * 256];
__device__ __align__(1024) __nv_bfloat16 g_U[640 * 2 * 2048];
__device__ __align__(1024) __nv_bfloat16 g_zT[640 * NGRP * 8];
__device__ __align__(1024) float g_gate[NGRP * 8];
__device__ __align__(1024) unsigned g_cnt[C_COUNT * 32];
#define TS(i) do { } while (0)
#define TSL(i) TS(i)
#define TSB(i) do { } while (0)

__device__ __forceinline__ uint32_t smem_u32(const void* p) { return (uint32_t)__cvta_generic_to_shared(p); }
__device__ __forceinline__ int fresh_lane() {
  int r;
  asm volatile("mov.u32 %0, %%laneid;" : "=r"(r));
  return r;
}
__device__ __forceinline__ uint64_t mkdesc(uint32_t addr, uint32_t lbo, uint32_t sbo, uint32_t swz) {
  return (uint64_t)((addr & 0x3FFFF) >> 4) | ((uint64_t)(lbo >> 4) << 16) | ((uint64_t)(sbo >> 4) << 32) | ((uint64_t)swz << 62);
}
__device__ __forceinline__ void wg_fence() { asm volatile("wgmma.fence.sync.aligned;" ::: "memory"); }
__device__ __forceinline__ void wg_commit() { asm volatile("wgmma.commit_group.sync.aligned;" ::: "memory"); }
template <int N> __device__ __forceinline__ void wg_wait() { asm volatile("wgmma.wait_group.sync.aligned %0;" ::"n"(N) : "memory"); }
template <int N> __device__ __forceinline__ void pin(float* d) {
#pragma unroll
  for (int i = 0; i < N; i++) asm volatile("" : "+f"(d[i])::"memory");
}
__device__ __forceinline__ void mbar_init(uint32_t a, int c) { asm volatile("mbarrier.init.shared::cta.b64 [%0], %1;" ::"r"(a), "r"(c) : "memory"); }
__device__ __forceinline__ void mbar_expect(uint32_t a, uint32_t b) { asm volatile("mbarrier.arrive.expect_tx.shared::cta.b64 _, [%0], %1;" ::"r"(a), "r"(b) : "memory"); }
__device__ __forceinline__ uint32_t peer_addr(uint32_t a) {
  uint32_t r;
  asm("mapa.shared::cluster.u32 %0, %1, %2;" : "=r"(r) : "r"(a), "r"((blockIdx.x & 1) ^ 1));
  return r;
}
__device__ __forceinline__ void mbar_arrive(uint32_t a) { asm volatile("mbarrier.arrive.shared::cta.b64 _, [%0];" ::"r"(a) : "memory"); }
__device__ __forceinline__ bool elect_one() {
  uint32_t e;
  asm volatile("{\n.reg .pred p;\nelect.sync _|p, 0xffffffff;\nselp.u32 %0,1,0,p;\n}" : "=r"(e));
  return e;
}
__device__ __forceinline__ void mbar_wait_t(uint32_t a, uint32_t ph) {
  asm volatile(
      "{\n.reg .pred p, q;\n.reg .u32 n;\n"
      "mbarrier.try_wait.parity.shared::cta.b64 p, [%0], %1;\n"
      "@p bra DONE_%=;\n"
      "mov.u32 n, 0;\n"
      "WAIT_%=:\n"
      "mbarrier.try_wait.parity.shared::cta.b64 p, [%0], %1;\n"
      "@p bra DONE_%=;\n"
      "add.u32 n, n, 1;\n"
      "setp.lt.u32 q, n, 0x40000;\n"
      "@q bra WAIT_%=;\n"
      "trap;\n"
      "DONE_%=:\n}" ::"r"(a), "r"(ph) : "memory");
}
__device__ __forceinline__ void mbar_wait(uint32_t a, uint32_t ph) {
  asm volatile(
      "{\n.reg .pred p, q;\n.reg .u32 n;\nmov.u32 n, 0;\n"
      "WAIT_%=:\n"
      "mbarrier.try_wait.parity.shared::cta.b64 p, [%0], %1;\n"
      "@p bra DONE_%=;\n"
      "add.u32 n, n, 1;\n"
      "setp.lt.u32 q, n, 0x80000;\n"
      "@q bra WAIT_%=;\n"
      "DONE_%=:\n}" ::"r"(a), "r"(ph) : "memory");
}
__device__ __forceinline__ void flag_wait(const unsigned* p0, const unsigned* p1, unsigned target) {
  int it = 0;
  while (true) {
    unsigned v0, v1;
    asm volatile("ld.relaxed.gpu.global.u32 %0, [%1];" : "=r"(v0) : "l"(p0) : "memory");
    asm volatile("ld.relaxed.gpu.global.u32 %0, [%1];" : "=r"(v1) : "l"(p1) : "memory");
    if (min(v0, v1) >= target) break;
    if (++it > (1 << 21)) __trap();
  }
  asm volatile("fence.proxy.async.global;" ::: "memory");
}
__device__ __forceinline__ void flag_add(unsigned* p) {
  asm volatile("red.relaxed.gpu.global.add.u32 [%0], 1;" ::"l"(p) : "memory");
}
__device__ __forceinline__ void bar_sync(int id, int n) { asm volatile("bar.sync %0, %1;" ::"r"(id), "r"(n) : "memory"); }
__device__ __forceinline__ void bar_arrive(int id, int n) { asm volatile("bar.arrive %0, %1;" ::"r"(id), "r"(n) : "memory"); }
__device__ __forceinline__ void bulk_g2s(uint32_t dst, const void* src, uint32_t bytes, uint32_t bar) {
  asm volatile("cp.async.bulk.shared::cluster.global.mbarrier::complete_tx::bytes [%0], [%1], %2, [%3];" ::"r"(dst), "l"(src), "r"(bytes), "r"(bar) : "memory");
}
__device__ __forceinline__ void bulk_s2g(void* dst, uint32_t src, uint32_t bytes) {
  asm volatile("cp.async.bulk.global.shared::cta.bulk_group [%0], [%1], %2;" ::"l"(dst), "r"(src), "r"(bytes) : "memory");
}
__device__ __forceinline__ void bulk_prefetch(const void* src, uint32_t bytes) {
  asm volatile("cp.async.bulk.prefetch.L2.global [%0], %1;" ::"l"(src), "r"(bytes) : "memory");
}
__device__ __forceinline__ void tma2(uint32_t dst, const CUtensorMap* m, int c0, int c1, uint32_t bar) {
  asm volatile("cp.async.bulk.tensor.2d.shared::cluster.global.mbarrier::complete_tx::bytes [%0], [%1, {%3,%4}], [%2];" ::"r"(dst), "l"(m), "r"(bar), "r"(c0), "r"(c1) : "memory");
}
__device__ __forceinline__ void tma3(uint32_t dst, const CUtensorMap* m, int c0, int c1, int c2, uint32_t bar) {
  asm volatile("cp.async.bulk.tensor.3d.shared::cluster.global.mbarrier::complete_tx::bytes [%0], [%1, {%3,%4,%5}], [%2];" ::"r"(dst), "l"(m), "r"(bar), "r"(c0), "r"(c1), "r"(c2) : "memory");
}
__device__ __forceinline__ void tma4(uint32_t dst, const CUtensorMap* m, int c0, int c1, int c2, int c3, uint32_t bar) {
  asm volatile("cp.async.bulk.tensor.4d.shared::cluster.global.mbarrier::complete_tx::bytes [%0], [%1, {%3,%4,%5,%6}], [%2];" ::"r"(dst), "l"(m), "r"(bar), "r"(c0), "r"(c1), "r"(c2), "r"(c3) : "memory");
}
__device__ __forceinline__ void prefetch_map(const CUtensorMap* m) { asm volatile("prefetch.tensormap [%0];" ::"l"(m) : "memory"); }
__device__ __forceinline__ void tma2_store(const CUtensorMap* m, uint32_t src, int c0, int c1) {
  asm volatile("cp.async.bulk.tensor.2d.global.shared::cta.bulk_group [%0, {%2,%3}], [%1];" ::"l"(m), "r"(src), "r"(c0), "r"(c1) : "memory");
}
__device__ __forceinline__ void tma3_store(const CUtensorMap* m, uint32_t src, int c0, int c1, int c2) {
  asm volatile("cp.async.bulk.tensor.3d.global.shared::cta.bulk_group [%0, {%2,%3,%4}], [%1];" ::"l"(m), "r"(src), "r"(c0), "r"(c1), "r"(c2) : "memory");
}
__device__ __forceinline__ void tma4_store(const CUtensorMap* m, uint32_t src, int c0, int c1, int c2, int c3) {
  asm volatile("cp.async.bulk.tensor.4d.global.shared::cta.bulk_group [%0, {%2,%3,%4,%5}], [%1];" ::"l"(m), "r"(src), "r"(c0), "r"(c1), "r"(c2), "r"(c3) : "memory");
}
__device__ __forceinline__ uint32_t pack_bf16(float lo, float hi) {
  uint32_t r;
  asm("cvt.rn.bf16x2.f32 %0, %1, %2;" : "=r"(r) : "f"(hi), "f"(lo));
  return r;
}
__device__ __forceinline__ float tanh_fast(float x) {
  float r;
  asm("tanh.approx.f32 %0, %1;" : "=f"(r) : "f"(x));
  return r;
}
__device__ __forceinline__ uint32_t bmul2(uint32_t a, uint32_t b) {
  uint32_t r;
  asm("mul.rn.bf16x2 %0, %1, %2;" : "=r"(r) : "r"(a), "r"(b));
  return r;
}
__device__ __forceinline__ uint32_t bfma2(uint32_t a, uint32_t b, uint32_t c) {
  uint32_t r;
  asm("fma.rn.bf16x2 %0, %1, %2, %3;" : "=r"(r) : "r"(a), "r"(b), "r"(c));
  return r;
}
__device__ __forceinline__ uint2 lds64(uint32_t a) {
  uint2 r;
  asm volatile("ld.volatile.shared.v2.u32 {%0,%1}, [%2];" : "=r"(r.x), "=r"(r.y) : "r"(a) : "memory");
  return r;
}
__device__ __forceinline__ float bflo(uint32_t v) { return __uint_as_float(v << 16); }
__device__ __forceinline__ float bfhi(uint32_t v) { return __uint_as_float(v & 0xffff0000u); }

__device__ __forceinline__ uint32_t badd2(uint32_t a, uint32_t b) {
  uint32_t r;
  asm("add.rn.bf16x2 %0, %1, %2;" : "=r"(r) : "r"(a), "r"(b));
  return r;
}
template <int I0, int I1, int REV = 0> __device__ __forceinline__ void conv_mma(float* d, uint64_t da, uint64_t db) {
  if constexpr (I0 < I1) {
    constexpr int S = REV && I0 >= 2 * REV ? 15 + REV - (I0 >> 1) : I0 >> 1, PH = I0 & 1;
    wgmma_ss<128 - 8 * S, 1, 1>(d, da + (PH * (H_PITCH >> 4) + 16 * S), db + (PH * 256 + 16 * S), I0 != 0);
    conv_mma<I0 + 1, I1, REV>(d, da, db);
  }
}
__device__ __forceinline__ uint64_t conv_da(int ch) { return mkdesc(SB0 + OFF_H + ch * 2 * H_PITCH, 128, 32, 0); }
__device__ __forceinline__ uint64_t conv_db(int ch) { return mkdesc(SB0 + OFF_U + (4 - ch) * 8192, 128, 256, 0); }
__device__ __forceinline__ void sts128_if(bool p, uint32_t a, const uint32_t* v) {
  asm volatile("{\n.reg .pred p;\nsetp.ne.u32 p, %5, 0;\n@p st.shared.v4.u32 [%0], {%1,%2,%3,%4};\n}" ::"r"(a), "r"(v[0]), "r"(v[1]), "r"(v[2]), "r"(v[3]), "r"((uint32_t)p) : "memory");
}
__device__ __forceinline__ void lds128_if(bool p, uint32_t a, uint32_t* v) {
  asm volatile("{\n.reg .pred p;\nsetp.ne.u32 p, %5, 0;\n@p ld.shared.v4.u32 {%0,%1,%2,%3}, [%4];\n}" : "+r"(v[0]), "+r"(v[1]), "+r"(v[2]), "+r"(v[3]) : "r"(a), "r"((uint32_t)p) : "memory");
}
__host__ __device__ constexpr int cvs(int next, int i) {
  constexpr int a[8] = {CV1}, b[8] = {CV4};
  return (next == 1 ? CV02 + a[i] : CV04 + b[i]) > 32 ? 32 : (next == 1 ? CV02 + a[i] : CV04 + b[i]);
}
template <int NEXT, int NF = 0>
__device__ __forceinline__ void conv_finish(const float* d, uint32_t sb, uint32_t bar, int ch, int wg, int w, float* dn, uint64_t da, uint64_t db) {
  const int lane = fresh_lane();
  const int g = lane >> 2, q = lane & 3;
  const int c = q & 1, mu = 8 * (q >> 1) + g;
  const int mu1 = (mu + 15) & 15, mu2 = (mu + (c ? 2 : 14)) & 15;
  const int src1 = 4 * (mu1 & 7) + 2 * (mu1 >> 3) + c;
  const int src2 = 4 * (mu2 & 7) + 2 * (mu2 >> 3) + (c ^ 1);
  const bool last = mu == 15, pA = (c == 0) || (mu >= 14);
  const bool impX = lane < 2, impY = (c == 1) && (mu >= 14);
  const int oo = 32 * w + (c ? mu2 : 16 + mu);
  const uint32_t zs = sb + zstage(ch);
  const uint32_t ex = sb + OFF_EX + (ch & 3) * 128 + (impX ? lane : 2 + (mu & 1)) * 32;
#define GO(N) if (NEXT == 2 && G2W == N && w == 0 && lane == 0) mbar_arrive(bar + 8 * B_GO);
  uint32_t p0[8], xr[8], s1[8], e[8];
#pragma unroll
  for (int k = 0; k < 8; k++) {
    const int i = 60 - 8 * k;
    const uint32_t p1 = pack_bf16(d[i + 1], d[i - 3]), p3 = pack_bf16(d[i + 3], d[i - 1]);
    s1[k] = badd2(pack_bf16(d[i + 2], d[i - 2]), __shfl_sync(0xffffffffu, last ? p1 : p3, src1));
    xr[k] = __shfl_sync(0xffffffffu, last ? p3 : p1, src1);
    p0[k] = pack_bf16(d[i], d[i - 4]);
    if (NEXT && k == 1) conv_mma<cvs(NEXT, 0), cvs(NEXT, 1), NEXT == 2 ? C4R : 0>(dn, da, db);
    if (NEXT && k == 3) conv_mma<cvs(NEXT, 1), cvs(NEXT, 2), NEXT == 2 ? C4R : 0>(dn, da, db);
    if (NEXT && k == 5) conv_mma<cvs(NEXT, 2), cvs(NEXT, 3), NEXT == 2 ? C4R : 0>(dn, da, db);
    if (NEXT && k == 7) conv_mma<cvs(NEXT, 3), cvs(NEXT, 4), NEXT == 2 ? C4R : 0>(dn, da, db);
  }
  GO(4)
  const uint32_t sh = w == 3 ? 0x5432 : 0x7654;
#pragma unroll
  for (int k = 0; k < 8; k++) e[k] = impX ? xr[k] : s1[k];
#pragma unroll
  for (int k = 7; k >= 0; k--) e[k] = __byte_perm(k ? e[k - 1] : 0u, e[k], sh);
  sts128_if(impX || impY, ex + ((w + 1) & 3) * 512, e);
  sts128_if(impX || impY, ex + ((w + 1) & 3) * 512 + 16, e + 4);
  if (NEXT) conv_mma<cvs(NEXT, 4), cvs(NEXT, 5), NEXT == 2 ? C4R : 0>(dn, da, db);
  bar_sync(3 + wg, 128);
  GO(5)
  if (w == 0 && lane == 0) mbar_arrive(bar + 8 * (B_CD + ch));
  lds128_if(impX, ex + w * 512, xr);
  lds128_if(impX, ex + w * 512 + 16, xr + 4);
  lds128_if(impY, ex + w * 512, s1);
  lds128_if(impY, ex + w * 512 + 16, s1 + 4);
  if (NEXT) conv_mma<cvs(NEXT, 5), cvs(NEXT, 6), NEXT == 2 ? C4R : 0>(dn, da, db);
  GO(6)
#pragma unroll
  for (int k = 0; k < 8; k++) {
    const uint32_t s0 = badd2(p0[k], xr[k]);
    e[k] = badd2(pA ? s1[k] : s0, __shfl_sync(0xffffffffu, pA ? s0 : s1[k], src2));
    if (NEXT && k == 3) conv_mma<cvs(NEXT, 6), cvs(NEXT, 7), NEXT == 2 ? C4R : 0>(dn, da, db);
  }
  GO(7)
  const uint32_t z0 = zs + oo * 4 + (oo / 20) * 240, z1 = zs + (oo + 130) * 4 + ((oo + 130) / 20) * 240;
#pragma unroll
  for (int k = 0; k < 8; k++) asm volatile("st.shared.u32 [%0], %1;" ::"r"((k < 4 ? z0 : z1) + (k & 3) * 80), "r"(e[k]) : "memory");
  if (!NF) asm volatile("fence.proxy.async.shared::cta;" ::: "memory");
  __syncwarp();
  if (lane == 0) mbar_arrive(bar + 8 * (B_SIGZ + ch));
  if (NEXT) { conv_mma<cvs(NEXT, 7), 32, NEXT == 2 ? C4R : 0>(dn, da, db); wg_commit(); }
  GO(8)
}
template <int S, int OWN, int K0 = 0, int K1 = 4> __device__ __forceinline__ void g2_half(float* acc, uint64_t dA, uint64_t dB, int sc) {
#pragma unroll
  for (int kk = K0; kk < K1; kk++)
    wgmma_ss<160, 1, 0>(acc, dA + (((OWN ? slotO(S) : slotF(S)) >> 4) + 128 * kk), dB + (((kk < 2 ? slotB0(S) : slotB1(S)) >> 4) + 2 * (kk & 1)), kk ? 1 : sc);
}

template <int I0, int I1> __device__ __forceinline__ void g2_own(float* acc, uint64_t dA, uint64_t dB, uint32_t bar) {
  if constexpr (I0 < I1 && I0 < 16) {
    if constexpr ((I0 & 3) == 0 && 8 + (I0 >> 2) >= ODK) { mbar_wait(bar + 8 * (B_O + (I0 >> 2)), 0); wg_fence(); }
    g2_half<((I0 >> 2) + 3) % 5, 1, I0 & 3, (I0 & 3) + 1>(acc, dA, dB, 1);
    g2_own<I0 + 1, I1>(acc, dA, dB, bar);
  }
}

template <int HF, int I0, int I1> __device__ __forceinline__ void g2_sp(float* acc, uint64_t dA, uint64_t dB) {
  if constexpr (I0 < I1 && I0 < 16) {
    constexpr int S = ((I0 >> 2) + 3) % 5, kk = I0 & 3;
    wgmma_ss<80, 1, 0>(acc, dA + ((slotO(S) >> 4) + 128 * kk), dB + (((kk < 2 ? slotB0(S) : slotB1(S)) >> 4) + 2 * (kk & 1) + 320 * HF), HF == 0 || I0 != 16 - NSP);
    g2_sp<HF, I0 + 1, I1>(acc, dA, dB);
  }
}

template <int PART> __device__ __forceinline__ void glu_part(const float* acc, uint32_t dst) {
  constexpr int h = PART & 1, aa = PART >> 1;
  uint32_t v[4];
#pragma unroll
  for (int jj = 0; jj < 4; jj++) {
    const int i = 4 * (4 * aa + jj) + 2 * h;
    float t0 = tanh_fast(0.5f * acc[i]), t1 = tanh_fast(0.5f * acc[i + 1]);
    v[jj] = pack_bf16(fmaf(acc[48 + i], t0, acc[48 + i]), fmaf(acc[49 + i], t1, acc[49 + i]));
  }
  asm volatile("stmatrix.sync.aligned.m8n8.x4.shared.b16 [%0], {%1,%2,%3,%4};" ::"r"(dst + h * 1536 + aa * 512), "r"(v[0]), "r"(v[1]), "r"(v[2]), "r"(v[3]) : "memory");
}

struct Params {
  const __nv_bfloat16* q0;
  unsigned char m4[40];
  unsigned char c2[72];
  const __nv_bfloat16 *gate_w, *k, *v, *shift_k, *q, *w_gate, *w_up, *w_down, *ssm_k, *ssm_D;
  unsigned char g2[72];
};

enum { mX, mWg, mWu, mU, mQ, mH, mWd, mZ, mO, mK, mV, mCOUNT };
struct Maps { CUtensorMap m[mCOUNT]; };

__global__ void __cluster_dims__(2, 1, 1) __launch_bounds__(384, 1)
fused_kernel(const Params P, const __grid_constant__ Maps M) {
  extern __shared__ __align__(1024) unsigned char sm[];
  const uint32_t sb = smem_u32(sm);
  const uint32_t bar = sb + OFF_BAR;
  const int tid = threadIdx.x, warp = __shfl_sync(0xffffffffu, tid >> 5, 0), lane = tid & 31;
#define CTA_ROLE()                                                                                           \
  const int rank = blockIdx.x & 1;               \
  const int cta = 2 * P.c2[blockIdx.x >> 1] + rank;                                                          \
  const bool has1 = cta < 128;                                                                               \
  const int mb = cta >> 4, ft = cta & 15;                                                        \
  (void)mb; (void)ft;
#define G2_ROLE()                                                                                            \
  const int g2 = P.g2[blockIdx.x >> 1];                                                                      \
  const int db = 2 * (g2 & 7) + rank;                                    \
  const int tb = g2 >> 3;                                                 \
  (void)db; (void)tb;

#define CA_C2 ((P.m4[blockIdx.x >> 2] << 3) >> (2 * (blockIdx.x & 2)))
#define CA_Q P.q0
#define CA_TOP()                                                                                                                      \
  {                                                                                                                                   \
    const int c2 = CA_C2, r = (tid >> 3) & 7;                                                                         \
    const char* gx = reinterpret_cast<const char*>(CA_Q) + (32 * (c2 & 32) + 4 * (c2 & 24) + 128 * r + (tid >> 6)) * 1280 + (tid & 7) * 16; \
    const uint32_t sx = sb + G1_STAGE + (tid >> 3) * 128 + (((tid & 7) ^ r) << 4);                                                   \
    asm volatile("{\n.reg .pred p;\nsetp.ne.u32 p, %2, 0;\n@p bra SK_%=;\n"                                                          \
                 CPA "[%0], [%1], 16;\n" CPA "[%0+4096], [%1+5120], 16;\n"                   \
                 CPA "[%0+16384], [%1+20480], 16;\n" CPA "[%0+20480], [%1+25600], 16;\n"     \
                 CPA "[%0+8192], [%1+10240], 16;\n" CPA "[%0+12288], [%1+15360], 16;\n"      \
                 CPA "[%0+24576], [%1+30720], 16;\n" CPA "[%0+28672], [%1+35840], 16;\n"     \
                 "SK_%=:\n}" ::"r"(sx), "l"(gx), "r"((c2 & 64) | (warp & 8)) : "memory");                                             \
    if (tid == 0) TS(2);                                                                                                              \
  }
  if (TOPO != 2 && warp == PMW && elect_one()) {
    if (!(CA0 & 1)) prefetch_map(&M.m[mX]);
    prefetch_map(&M.m[mWg]);
    prefetch_map(&M.m[mWu]);
    if (CA0 & 1) prefetch_map(&M.m[mX]);
    TS(77);
  }
  __syncwarp();
  {
    int t2;
    asm volatile("mov.u32 %0, %%tid.x;" : "=r"(t2));
    if (t2 < 256) {
      CA_TOP()
    }
  }
  if (warp < 8) {
#define CA_LOAD()                                                                                                                     \
    if (has1) {                                                                                                                       \
      const int r = (tid >> 3) & 7;                                                                                                   \
      const char* gx = reinterpret_cast<const char*>(P.q) + (1024 * (mb >> 2) + 128 * r + (mb & 3) * 32 + (tid >> 6)) * 1280 + (tid & 7) * 16; \
      const uint32_t sx = sb + G1_STAGE + (tid >> 3) * 128 + (((tid & 7) ^ r) << 4);                                                  \
      const int wo = (tid >> 2) * 3072 + ft * 192 + (tid & 3) * 16;                                                                   \
      const char *gg = reinterpret_cast<const char*>(P.w_gate) + wo, *gu = reinterpret_cast<const char*>(P.w_up) + wo;                \
      const uint32_t sw = sb + G1_STAGE + 32768 + (tid >> 2) * 64 + (((tid ^ (tid >> 3)) & 3) << 4);                                  \
      if (CA0 & 2) { _Pragma("unroll") for (int i = 0; i < 3; i++) {                                                                  \
        asm volatile("cp.async.cg.shared.global [%0], [%1], 16;" ::"r"(sw + i * 4096), "l"(gg + i * 64) : "memory");                  \
        asm volatile("cp.async.cg.shared.global [%0], [%1], 16;" ::"r"(sw + 12288 + i * 4096), "l"(gu + i * 64) : "memory"); } }      \
      if (CA0 & 1) { _Pragma("unroll") for (int i = 0; i < 8; i++)                                                                    \
        asm volatile("cp.async.cg.shared.global [%0], [%1], 16;" ::"r"(sx + i * 4096), "l"(gx + i * 5120) : "memory"); }              \
      if (tid == 0) TS(2);                                                                                                            \
    }
    CTA_ROLE();
    if (CA0 & 4) { CA_LOAD() }
    if (!HI && lane == 0) {
#pragma unroll
      for (int j = 0; j < 6; j++) mbar_init(bar + 8 * (B_FULL2 + j) + 48 * warp, (0x44321111u >> (4 * warp)) & 7);
      if (warp < 6 + (CA0 != 0 && !CAS)) mbar_init(bar + 8 * (B_O + warp), warp == 6 ? 8 : 1);
      if (warp < 4) mbar_expect(bar + 8 * (B_O + warp), 8192);
      if (!CAS) asm volatile("fence.proxy.async.shared::cta;" ::: "memory");
    }
    __syncwarp();
    if (!(CA0 & 124)) { CA_LOAD() }
    if (HI < 2) asm volatile("setmaxnreg.inc.sync.aligned.u32 224;");
    if (CA0 & 8) { CA_LOAD() }
    if (tid == 0) TS(8);
    if (CAS) asm volatile("cp.async.wait_all;\nfence.proxy.async.shared::cta;" ::: "memory");
    bar_arrive(1, 384);
    wg_fence();
    wg_commit();
    if (HI == 2) asm volatile("setmaxnreg.inc.sync.aligned.u32 224;");
    bar_sync(0, 384);
    if (DMZ) wg_wait<0>();
    if (HI == 3) asm volatile("setmaxnreg.inc.sync.aligned.u32 224;");
    asm volatile("barrier.cluster.arrive.relaxed.aligned;" ::: "memory");
    const int wg = (warp >> 2) ^ SWP, w = warp & 3;
    const bool elect = (tid & 127) == 0;
    if (tid == 0) TS(11);
    if (has1) {
      const int lane = fresh_lane();
      float acc0[96], acc1[96];
      float *const d0 = acc0, *const d1 = acc1;
      {
        const uint64_t dA = mkdesc(G1SB + wg * 16384, 16, 1024, 1);
        const uint64_t dB = mkdesc(G1SB + 32768, WH ? 2048 : 4096, 512, 2);
#pragma unroll 1
        for (int kb = 0; kb < 8; kb++) {
          const int rg = (kb + 1) % 3;
          const uint64_t da = dA + rg * (G1_STAGE >> 4), db = dB + rg * (G1_STAGE >> 4);
          if (tid == 0 && kb >= 6) TSB(70 + kb);
          mbar_wait(bar + 8 * (WH >= 2 && kb == 0 ? 58 : B_FULL1 + rg), (kb / 3) & 1);
          if (tid == 0) TS(kb == 0 ? 1 : 46 + kb);
          wg_fence();
#pragma unroll
          for (int kk = 0; kk < REL; kk++) wgmma_ss<192, 0, 1>(acc0, da + 2 * kk, db + WKO(kk), (kb | kk) != 0);
          wg_commit();
          wg_wait<1>();
          if (kb > 0 && elect) mbar_arrive(bar + 8 * (B_EMPTY1 + kb % 3));
          if (WH == 2) mbar_wait(bar + 8 * (B_FULL1 + rg), (kb / 3) & 1);
          wg_fence();
#pragma unroll
          for (int kk = REL; kk < 4; kk++) wgmma_ss<192, 0, 1>(acc0, da + 2 * kk, db + WKO(kk), 1);
#pragma unroll
          for (int kk = 0; kk < 4; kk++) wgmma_ss<192, 0, 1>(acc1, da + 512 + 2 * kk, db + WKO(kk), (kb | kk) != 0);
          wg_commit();
        }
#define G1_MMA(ACC, J) wgmma_ss<192, 0, 1>(ACC == 0 ? acc0 : acc1, dA + (((J) >> 2) * (G1_STAGE >> 4) + ACC * 512 + 2 * ((J) & 3)), dB + (((J) >> 2) * (G1_STAGE >> 4) + WKO((J) & 3)), 1)
        if (tid == 0) TS(124);
        mbar_wait(bar + 8 * (B_FULL1 + 0), 0);
        if (tid == 0) TS(125);
        wg_fence();
#pragma unroll
        for (int j = 0; j < REL; j++) G1_MMA(0, j);
        wg_commit();
        wg_wait<1>();
        if (elect) mbar_arrive(bar + 8 * B_R2FREE);
        wg_fence();
#pragma unroll
        for (int j = REL; j < 4; j++) G1_MMA(0, j);
#pragma unroll
        for (int j = 0; j < TLA; j++) G1_MMA(1, j);
        if (tid == 0) TS(46);
        mbar_wait(bar + 8 * (B_FULL1 + 1), 1);
        if (tid == 0) TS(95);
        wg_fence();
#pragma unroll
        for (int j = 4; j < 8; j++) G1_MMA(0, j);
        wg_commit();
#pragma unroll
        for (int j = TLA; j < TLA + 2; j++) G1_MMA(1, j);
        wg_commit();
        const uint32_t hd = sb + (w >> 1) * G1_STAGE + wg * 16384 + (w & 1) * 3072 + (lane & 7) * 64 + (((lane >> 3) ^ ((lane & 7) >> 1)) << 4);
        mbar_wait(bar + 8 * B_GATE, 0);
        if (UW == 3) mbar_wait(bar + 8 * (B_UFULL + wg), 0);
        wg_wait<1>();
        pin<96>(acc0);
        if (elect) TSB(2 + wg);
        wg_fence();
        if (TLA + 2 < 8) G1_MMA(1, TLA + 2);
        glu_part<0>(acc0, hd);
        if (TLA + 3 < 8) G1_MMA(1, TLA + 3);
        glu_part<1>(acc0, hd);
        if (TLA + 4 < 8) G1_MMA(1, TLA + 4);
        glu_part<2>(acc0, hd);
        if (TLA + 5 < 8) G1_MMA(1, TLA + 5);
        if (UW == 2) mbar_wait(bar + 8 * (B_UFULL + wg), 0);
        glu_part<3>(acc0, hd);
        if (TLA + 6 < 8) G1_MMA(1, TLA + 6);
        glu_part<4>(acc0, hd);
        if (TLA + 7 < 8) G1_MMA(1, TLA + 7);
        wg_commit();
        if (UW == 1) mbar_wait(bar + 8 * (B_UFULL + wg), 0);
        glu_part<5>(acc0, hd);
        if (!(FC & 1)) asm volatile("fence.proxy.async.shared::cta;" ::: "memory");
        __syncwarp();
        if (lane == 0) mbar_arrive(bar + 8 * (B_SIGH + 2 * wg));
        if (elect) TSB(6 + wg);
        const uint64_t ca = conv_da(wg), cb = conv_db(wg);
        if (!UW) mbar_wait(bar + 8 * (B_UFULL + wg), 0);
        if (elect) TS(10 + 3 * wg);
        wg_fence();
        conv_mma<0, CV0>(d0, ca, cb);
        wg_commit();
        wg_wait<1>();
        pin<96>(acc1);
        if (elect) mbar_arrive(bar + 8 * B_G1DONE);
        wg_fence();
        constexpr int gs[7] = {GL1};
        conv_mma<CV0 + gs[0], CV0 + gs[1]>(d0, ca, cb);
        glu_part<0>(acc1, hd + 8192);
        conv_mma<CV0 + gs[1], CV0 + gs[2]>(d0, ca, cb);
        glu_part<1>(acc1, hd + 8192);
        conv_mma<CV0 + gs[2], CV0 + gs[3]>(d0, ca, cb);
        glu_part<2>(acc1, hd + 8192);
        conv_mma<CV0 + gs[3], CV0 + gs[4]>(d0, ca, cb);
        glu_part<3>(acc1, hd + 8192);
        conv_mma<CV0 + gs[4], CV0 + gs[5]>(d0, ca, cb);
        glu_part<4>(acc1, hd + 8192);
        conv_mma<CV0 + gs[5], CV0 + gs[6]>(d0, ca, cb);
        glu_part<5>(acc1, hd + 8192);
        if (!(FC & 2)) asm volatile("fence.proxy.async.shared::cta;" ::: "memory");
        __syncwarp();
        if (lane == 0) mbar_arrive(bar + 8 * (B_SIGH + 2 * wg + 1));
        if (elect) TS(4 + wg);
        conv_mma<CV0 + gs[6], 32>(d0, ca, cb);
        wg_commit();
      }
      {
        const uint64_t ca = conv_da(wg + 2), cb = conv_db(wg + 2);
        mbar_wait(bar + 8 * (B_UFULL + wg + 2), 0);
        if (elect) TS(16 + 3 * wg);
        wg_fence();
        conv_mma<0, CV02>(d1, ca, cb);
        wg_commit();
        wg_wait<1>();
        pin<64>(d0);
        if (elect) TSB(11 + 3 * wg);
        wg_fence();
        conv_finish<1, FZ & 1>(d0, sb, bar, wg, wg, w, d1, ca, cb);
        if (!S0M && !CA0 && elect) TS(12 + 3 * wg);
      }
      if (wg == 0) {
        const uint64_t ca = conv_da(4), cb = conv_db(4);
        mbar_wait(bar + 8 * (B_UFULL + 4), 0);
        if (elect) TS(22);
        wg_fence();
        conv_mma<0, CV04, C4R>(d0, ca, cb);
        wg_commit();
        wg_wait<1>();
        pin<64>(d1);
        if ((CDE & 1) && (tid & 31) == 0) mbar_arrive(bar + 8 * B_CE);
        if (elect) TSB(17);
        wg_fence();
        conv_finish<2, FZ & 4>(d1, sb, bar, 2, wg, w, d0, ca, cb);
        if (elect) TS(18);
        wg_wait<0>();
        pin<64>(d0);
        if ((CDE & 2) && (tid & 31) == 0) mbar_arrive(bar + 8 * (B_CE + 1));
        if (elect) TS(23);
        conv_finish<0, FZ & 16>(d0, sb, bar, 4, wg, w, d0, ca, cb);
        if (elect) TS(24);
      } else {
        wg_wait<0>();
        pin<64>(d1);
        if (elect) TS(20);
        conv_finish<0, FZ & 8>(d1, sb, bar, 3, wg, w, d1, 0, 0);
        if (elect) TS(21);
        if (G2W) mbar_wait(bar + 8 * B_GO, 0);
      }
    }
    const int lane = fresh_lane();
    const uint32_t xo = w * 512 + lane * 16;
    if (wg == 1) {
      float accF[80], accO[80];
      const uint64_t dA = mkdesc(SB0, 1024, 1024, 1);
      const uint64_t dB = mkdesc(SB0, 16, 512, 2);
#define G2_STAGE(S)                                                              \
      if (elect) TS(80 + 5 * r + S);                                             \
      mbar_wait(bar + 8 * (B_FULL2 + S), r);                                     \
      if (elect) TS(64 + 5 * r + S);                                             \
      wg_fence();                                                                \
      g2_half<S, 0, 0, REL2>(accF, dA, dB, (r | S) != 0);                        \
      wg_commit();                                                               \
      wg_wait<1>();                                                              \
      if ((r | S) != 0 && elect) mbar_arrive(bar + 8 * (B_EMPTY2 + (S + 4) % 5)); \
      wg_fence();                                                                \
      g2_half<S, 0, REL2, 4>(accF, dA, dB, 1);                                   \
      g2_half<S, 1>(accO, dA, dB, (r | S) != 0);                                 \
      wg_commit();
#pragma unroll 1
      for (int r = 0; r < 2; r++) {
        G2_STAGE(0) G2_STAGE(1) G2_STAGE(2)
        if (r) break;
        G2_STAGE(3) G2_STAGE(4)
      }
      uint32_t av[40], om[20], p[40];
      mbar_wait(bar + 8 * (B_FULL2 + 3), 1);
      if (elect) TS(72);
      wg_fence();
      g2_half<3, 0, 0, REL2>(accF, dA, dB, 1);
      wg_commit();
      wg_wait<1>();
      if ((tid & 126) == 0) mbar_arrive(bar + 8 * B_ZF);
      wg_fence();
      g2_half<3, 0, REL2, 4>(accF, dA, dB, 1);
      g2_own<0, TM8>(accO, dA, dB, bar);
      mbar_wait(bar + 8 * (B_FULL2 + 4), 1);
      if (elect) TS(73);
      wg_fence();
      g2_half<4, 0>(accF, dA, dB, 1);
      g2_own<TM8, TM9>(accO, dA, dB, bar);
      mbar_wait(bar + 8 * (B_FULL2 + 0), 0);
      if (elect) TS(74);
      wg_fence();
      g2_half<0, 0>(accF, dA, dB, 1);
      g2_own<TM9, TM10>(accO, dA, dB, bar);
      mbar_wait(bar + 8 * B_QG, 0);
#pragma unroll
      for (int j = 0; j < 20; j++) asm volatile("ld.shared.u32 %0, [%1];" : "=r"(om[j]) : "r"(sb + OFF_G + j * 32 + 16 + 4 * (lane & 3)) : "memory");
      mbar_wait(bar + 8 * B_XF, 0);
      mbar_wait(bar + 8 * (B_FULL2 + 1), 0);
      if (elect) TS(75);
      wg_fence();
      g2_half<1, 0>(accF, dA, dB, 1);
      wg_commit();
      g2_own<TM10, TM10 + 2>(accO, dA, dB, bar);
      wg_commit();
      {
        const uint32_t xd = peer_addr(sb + OFF_XCH + xo), xb = peer_addr(bar + 8 * B_XCH);
        const int i8 = lane & 7, mi = lane >> 3;
        const uint32_t oa = sb + OFF_OUT + ((mi >> 1) * 8 + i8) * 128 + (((2 * w + (mi & 1)) ^ i8) << 4);
        wg_wait<1>();
        pin<80>(accF);
        if (elect) TS(36);
        wg_fence();
#define AV_LOAD(I0, I1)                                                                                                                             \
        _Pragma("unroll") for (int i = I0; i < I1; i++)                                                                                             \
          asm volatile("ld.shared.v4.u32 {%0,%1,%2,%3}, [%4];" : "=r"(av[4 * i]), "=r"(av[4 * i + 1]), "=r"(av[4 * i + 2]), "=r"(av[4 * i + 3])     \
                       : "r"(sb + zbox(2 * w + i / 5) + lane * 16 + (i % 5) * 512) : "memory");
#define G2_SEND(I)                                                                                                                                  \
        asm volatile("st.async.shared::cluster.mbarrier::complete_tx::bytes.v4.b32 [%0], {%1,%2,%3,%4}, [%5];" ::"r"(xd + (I) * 2048),              \
                     "r"(pack_bf16(accF[8 * (I)], accF[8 * (I) + 1])), "r"(pack_bf16(accF[8 * (I) + 2], accF[8 * (I) + 3])),                        \
                     "r"(pack_bf16(accF[8 * (I) + 4], accF[8 * (I) + 5])), "r"(pack_bf16(accF[8 * (I) + 6], accF[8 * (I) + 7])),                    \
                     "r"(xb + ((I) / 5) * 8) : "memory");                                                                                           \
        if ((I) == AVS) { __syncwarp(); bar_sync(6, 256); }                                                                                         \
        if ((I) >= AVS) { AV_LOAD(((I) - AVS) * 10 / (AVS < 10 ? 10 - AVS : 1), ((I) + 1 - AVS) * 10 / (AVS < 10 ? 10 - AVS : 1)) }                 \
        g2_own<TM10 + 2 + (I) * SPN / SPD, TM10 + 2 + ((I) + 1) * SPN / SPD>(accO, dA, dB, bar);
        G2_SEND(0) G2_SEND(1) G2_SEND(2) G2_SEND(3) G2_SEND(4)
        static_assert(TM10 + 2 + 5 * SPN / SPD >= 4 && (ZN || AVS == 10), "");
        if (!ZN) wg_commit();
        G2_SEND(5) G2_SEND(6) G2_SEND(7) G2_SEND(8) G2_SEND(9)
        if (elect) TS(37);
        g2_own<TM10 + 2 + 10 * SPN / SPD, 16>(accO, dA, dB, bar);
        wg_commit();
        if (!ZN) wg_wait<1>();
        if (AVS == 10) {
          __syncwarp();
          bar_sync(6, 256);
          if (elect) TS(78);
          AV_LOAD(0, 10)
        }
        if (elect) TS(38);
#pragma unroll
        for (int hf = 0; hf < 2; hf++) {
          if (hf == 0 || !P1E) {
            mbar_wait(bar + 8 * (B_XCH + hf), 0);
            if (elect) TS(hf ? 59 : 31);
#pragma unroll
            for (int i = 5 * hf; i < 5 * hf + 5; i++)
              asm volatile("ld.shared.v4.u32 {%0,%1,%2,%3}, [%4];" : "=r"(p[4 * i]), "=r"(p[4 * i + 1]), "=r"(p[4 * i + 2]), "=r"(p[4 * i + 3]) : "r"(sb + OFF_XCH + xo + i * 2048) : "memory");
          }
          if (hf == 0 && P1E) {
            mbar_wait(bar + 8 * (B_XCH + 1), 0);
            if (elect) TS(59);
#pragma unroll
            for (int i = 5; i < 10; i++)
              asm volatile("ld.shared.v4.u32 {%0,%1,%2,%3}, [%4];" : "=r"(p[4 * i]), "=r"(p[4 * i + 1]), "=r"(p[4 * i + 2]), "=r"(p[4 * i + 3]) : "r"(sb + OFF_XCH + xo + i * 2048) : "memory");
          }
          if (hf == 0) {
            wg_wait<0>();
            pin<80>(accO);
            if (elect) TS(28);
          }
#pragma unroll
          for (int i = 20 * hf; i < 20 * hf + 20; i++) p[i] = bfma2(badd2(pack_bf16(accO[2 * i], accO[2 * i + 1]), p[i]), om[i >> 1], av[i]);
#pragma unroll
          for (int i = 5 * hf; i < 5 * hf + 5; i++)
            asm volatile("stmatrix.sync.aligned.m8n8.x4.trans.shared.b16 [%0], {%1,%2,%3,%4};" ::"r"(oa + i * 2048), "r"(p[4 * i]), "r"(p[4 * i + 1]), "r"(p[4 * i + 2]), "r"(p[4 * i + 3]) : "memory");
          if (!((FW >> hf) & 1)) asm volatile("fence.proxy.async.shared::cta;" ::: "memory");
          if (elect) TS(57 + hf);
          __syncwarp();
          bar_arrive(8 + hf, 160);
        }
      }
    } else {
      G2_ROLE();
      const int q = lane & 3, i8 = lane & 7, mi = lane >> 3;
      const uint32_t qa = sb + OFF_Q + ((mi >> 1) * 8 + i8) * 128 + (((2 * w + (mi & 1)) ^ i8) << 4);
      const uint32_t za = (lane >> 2) * 320 + q * 80, zb[2] = {sb + zbox(2 * w), sb + zbox(2 * w + 1)};
      uint32_t qv[40], av[40];
      mbar_wait(bar + 8 * B_QG, 0);
#pragma unroll
      for (int jp = 0; jp < 10; jp++)
        asm volatile("ldmatrix.sync.aligned.m8n8.x4.trans.shared.b16 {%0,%1,%2,%3}, [%4];" : "=r"(qv[4 * jp]), "=r"(qv[4 * jp + 1]), "=r"(qv[4 * jp + 2]), "=r"(qv[4 * jp + 3]) : "r"(qa + jp * 2048) : "memory");
#pragma unroll
      for (int j = 0; j < 20; j++) {
        const uint32_t g2 = *reinterpret_cast<const uint32_t*>(sm + OFF_G + j * 32 + 4 * q);
        qv[2 * j] = bmul2(qv[2 * j], g2);
        qv[2 * j + 1] = bmul2(qv[2 * j + 1], g2);
      }
#pragma unroll
      for (int i = 0; i < 40; i++) asm volatile("" : "+r"(qv[i])::"memory");
      __syncwarp();
      if (lane == 0) mbar_arrive(bar + 8 * B_QC);
      if (elect) TS(60);
      mbar_wait(bar + 8 * B_Z, 0);
      if (elect) TS(27);
#pragma unroll
      for (int i = 0; i < 10; i++)
        asm volatile("ld.shared.v4.u32 {%0,%1,%2,%3}, [%4];" : "=r"(av[8 * (i >> 1) + (i & 1)]), "=r"(av[8 * (i >> 1) + 2 + (i & 1)]), "=r"(av[8 * (i >> 1) + 4 + (i & 1)]), "=r"(av[8 * (i >> 1) + 6 + (i & 1)])
                     : "r"(zb[i & 1] + za + (i >> 1) * 16) : "memory");
#pragma unroll
      for (int i = 0; i < 40; i++) av[i] = bmul2(av[i], qv[i]);
      __syncwarp();
#pragma unroll
      for (int i = 0; i < 10; i++)
        asm volatile("st.shared.v4.b32 [%0], {%1,%2,%3,%4};" ::"r"(zb[i / 5] + lane * 16 + (i % 5) * 512), "r"(av[4 * i]), "r"(av[4 * i + 1]), "r"(av[4 * i + 2]), "r"(av[4 * i + 3]) : "memory");
      if (elect) TS(29);
      __syncwarp();
      bar_arrive(6, 256);
      if (!W2S && w == 0) {
#pragma unroll
        for (int hf = 0; hf < 2; hf++) {
          bar_sync(8 + hf, 160);
          if ((FW >> hf) & 1) asm volatile("fence.proxy.async.shared::cta;" ::: "memory");
          if (elect_one()) tma4_store(&M.m[mO], sb + OFF_OUT + hf * 10240, db * 64, 0, ((2 * tb + hf) % 13) * 10, (2 * tb + hf) / 13);
          __syncwarp();
        }
        if (elect) TS(26);
        asm volatile("cp.async.bulk.commit_group;" ::: "memory");
        asm volatile("cp.async.bulk.wait_group.read 0;" ::: "memory");
      }
      if (elect) {
        TSL(30);
      }
    }
  } else {
    if (TOPO != 4) asm volatile("setmaxnreg.dec.sync.aligned.u32 56;");
    if (TOPO == 4 && warp == 8 && lane == 0) {
      mbar_expect(bar + 8 * (B_FULL1 + 0), G1_STAGE);
      mbar_expect(bar + 8 * (B_FULL1 + 2), G1_STAGE);
      mbar_expect(bar + 8 * B_KV, 23040 + 21760 + 640);
    }
    if (TOPO != 4 && warp == 8 && lane == 0) {
#pragma unroll
      for (int rg = 0; rg < 3 + !KVLD; rg++) if (TOPO != 3 || rg != 1) mbar_init(bar + 8 * (B_FULL1 + rg), 1);
#pragma unroll
      for (int rg = 0; rg < 3; rg++) if (TOPO != 3 || rg != 1) mbar_expect(bar + 8 * (B_FULL1 + rg), G1_STAGE + (rg == 1 ? (GWB ? 0 : 1280) - (WH >= 2 ? 12288 : 0) - (S0M || (CA0 & 2) ? 24576 : 0) - (CA0 & 1 ? 32768 : 0) : 0));
      if (!KVLD) mbar_expect(bar + 8 * B_KV, 23040 + 21760 + 640);
      if (GWB) { mbar_init(bar + 8 * 58, 1); mbar_expect(bar + 8 * 58, 1280); }
      if (WH >= 2) { mbar_init(bar + 8 * 58, 1); mbar_expect(bar + 8 * 58, 12288); }
      asm volatile("fence.proxy.async.shared::cta;" ::: "memory");
      TS(76);
    }
    if (HI && warp > 8 && lane < 19) {
      static_assert(!HI || ODK == 12, "");
      const int i = 19 * (warp - 9) + lane;
      mbar_init(bar + 8 * B_FULL2 + 8 * i, (uint32_t)(0x8144321111ull >> (4 * (i / 6))) & 15);
      asm volatile("fence.proxy.async.shared::cta;" ::: "memory");
    }
    __syncwarp();
    bar_arrive(warp == 8 ? 0 : 1, 384);
    if (warp != 8) bar_sync(0, 384);
    CTA_ROLE();
    if (warp == 8) {
      if (has1 && elect_one()) {
        TS(126);
#define G1_LOAD(KB, RG)                                                                                              \
        tma4(sb + (RG) * G1_STAGE, &M.m[mX], (KB) * 64, 0, (mb & 3) * 32, mb >> 2, bar + 8 * (B_FULL1 + (RG)));      \
        W_LOAD(sb + (RG) * G1_STAGE, KB, bar + 8 * (B_FULL1 + (RG)), bar + 8 * (B_FULL1 + (RG)))
#define W_LOAD(DST, KB, B0, B1)                                                                                      \
        tma3((DST) + 32768, &M.m[mWg], 0, (KB) * 64, ft * 3, B0);                                                    \
        tma3((DST) + (WH ? 38912 : 45056), &M.m[mWu], 0, (KB) * 64, ft * 3, B0);                                     \
        if (WH) {                                                                                                    \
          tma3((DST) + 45056, &M.m[mWg], 0, (KB) * 64 + 32, ft * 3, B1);                                             \
          tma3((DST) + 51200, &M.m[mWu], 0, (KB) * 64 + 32, ft * 3, B1);                                             \
        }
        if (!(CA0 & 1)) tma4(sb + G1_STAGE, &M.m[mX], 0, 0, (mb & 3) * 32, mb >> 2, bar + 8 * (B_FULL1 + 1));
        if (!(CA0 & 2) && TOPO < 3) {
          W_LOAD(sb + G1_STAGE, 0, bar + 8 * (WH >= 2 ? 58 : B_FULL1 + 1), bar + 8 * (B_FULL1 + 1))
        }
        if (TOPO < 3) TSL(127);
      }
      if (has1 && elect_one()) {
        static_assert(!GWB || (CAS && TOPO < 3), "");
        if (TOPO != 3 && GWB < 2) bulk_g2s(sb + OFF_EX + 640, P.gate_w, 1280, bar + 8 * (GWB ? 58 : B_FULL1 + 1));
#define SPIN(N) if (N) { unsigned c0, c1; asm volatile("mov.u32 %0, %%clock;" : "=r"(c0)); do { asm volatile("mov.u32 %0, %%clock;" : "=r"(c1)); } while (c1 - c0 < N); }
        SPIN(D1)
        G1_LOAD(1, 2);
        if (GWB == 2) bulk_g2s(sb + OFF_EX + 640, P.gate_w, 1280, bar + 8 * 58);
        SPIN(D2)
        if (!S2W) { G1_LOAD(2, 0); }
        TSL(6);
      }
      __syncwarp();
      if (S2W && has1) {
        mbar_wait_t(bar + 8 * (B_FULL1 + 1), 0);
        if (elect_one()) { G1_LOAD(2, 0); }
      }
      __syncwarp();
      bar_sync(1, 384);
    } else if (elect_one()) {
      prefetch_map(&M.m[warp == 9 ? mU : warp - 5]);
    }
    if (lane == 0 && warp < 10) TSL(warp == 8 ? 14 : 17);
    __syncwarp();
    if (warp != 11) asm volatile("barrier.cluster.arrive.relaxed.aligned;" ::: "memory");
    if (warp == 8) {
      if (has1) {
#define V_COPY() tma3(sb + OFF_V, &M.m[mV], (cta & 7) * 80, (cta >> 3) * 16 - 1, 0, bar + 8 * B_KV);
#define KV_COPY()                                                                                    \
          tma3(sb + OFF_H, &M.m[mK], (cta & 7) * 80, (cta >> 3) * 16 - 2, 0, bar + 8 * B_KV);             \
          if (VAT <= KVAT) { V_COPY() }                                                                \
          bulk_g2s(sb + OFF_EX, P.shift_k + (cta & 7) * 320, 640, bar + 8 * B_KV);
        if (elect_one()) {
          KV_COPY();
        }
        if (((CA0 & 1) && !CAS) || GWB) mbar_wait_t(bar + 8 * 58, 0);
        float s[4] = {0.f, 0.f, 0.f, 0.f};
        const uint32_t xa = sb + ft * 2048 + (lane >> 3) * 128;
#pragma unroll 1
        for (int kb = 2; kb < 12; kb++) {
          const int kg = kb - 2, rg = (kb - 1) % 3;
          if (kb >= 3 && kb < 10) {
            const int rl = (kb + 1) % 3;
            const uint32_t dst = sb + rl * G1_STAGE, fb = bar + 8 * (B_FULL1 + rl);
            mbar_wait_t(bar + 8 * (B_EMPTY1 + rl), (kb / 3 - 1) & 1);
            if (elect_one()) {
              tma4(dst, &M.m[mX], kb * 64, 0, (mb & 3) * 32, mb >> 2, fb);
              W_LOAD(dst, kb, fb, fb)
              if (kb == KVAT) { KV_COPY(); }
              if (VAT > KVAT && kb == VAT) { V_COPY(); }
              TSL(85 + kb);
            }
          } else {
            mbar_wait_t(bar + 8 * (B_FULL1 + rg), (kg / 3) & 1);
            if (VAT == 2 && kb == 2) {
              if (VW) mbar_wait_t(bar + 8 * (B_FULL1 + (VW == 1 ? 2 : 0)), 0);
              if (elect_one()) { V_COPY(); }
            }
          }
          uint4 xv[4], gw;
#pragma unroll
          for (int i = 0; i < 4; i++)
            asm volatile("ld.shared.v4.u32 {%0,%1,%2,%3}, [%4];" : "=r"(xv[i].x), "=r"(xv[i].y), "=r"(xv[i].z), "=r"(xv[i].w)
                         : "r"(xa + rg * G1_STAGE + i * 512 + (((lane & 7) ^ ((lane >> 3) + 4 * (i & 1))) << 4)) : "memory");
          asm volatile("ld.shared.v4.u32 {%0,%1,%2,%3}, [%4];" : "=r"(gw.x), "=r"(gw.y), "=r"(gw.z), "=r"(gw.w) : "r"(sb + OFF_EX + 640 + kg * 128 + (lane & 7) * 16) : "memory");
          if (lane == 0 && kg < 7) mbar_expect(bar + 8 * (B_FULL1 + rg), G1_STAGE);
          if (kb == PFK && elect_one()) bulk_prefetch(P.ssm_k + (size_t)cta * 5 * 2048, 20480);
          if (kb == PFW && elect_one()) bulk_prefetch(P.w_down + (size_t)cta * 7680, 15360);
#pragma unroll
          for (int i = 0; i < 4; i++) {
            const uint32_t p0 = bmul2(xv[i].x, gw.x), p1 = bmul2(xv[i].y, gw.y), p2 = bmul2(xv[i].z, gw.z), p3 = bmul2(xv[i].w, gw.w);
            s[i] += (bflo(p0) + bfhi(p0)) + (bflo(p1) + bfhi(p1)) + ((bflo(p2) + bfhi(p2)) + (bflo(p3) + bfhi(p3)));
          }
          pin<4>(s);
          __syncwarp();
          if (kg == 7 && lane == 0) mbar_arrive(bar + 8 * B_R2FREE);
        }
        if (lane == 0) { mbar_arrive(bar + 8 * B_GATE); TS(44); }
        float s0 = (lane & 4) ? s[2] : s[0], s1 = (lane & 4) ? s[3] : s[1];
        s0 += __shfl_xor_sync(0xffffffffu, (lane & 4) ? s[0] : s[2], 4);
        s1 += __shfl_xor_sync(0xffffffffu, (lane & 4) ? s[1] : s[3], 4);
        float sv = (lane & 2) ? s1 : s0;
        sv += __shfl_xor_sync(0xffffffffu, (lane & 2) ? s0 : s1, 2);
        sv += __shfl_xor_sync(0xffffffffu, sv, 1);
        sv = __bfloat162float(__float2bfloat16(sv));
        sv = __bfloat162float(__float2bfloat16(1.f / (1.f + __expf(-sv))));
        reinterpret_cast<__nv_bfloat16*>(sm + OFF_GS)[(lane & 4) * 4 + (lane & 1) * 8 + (lane & 2) * 2 + (lane >> 3)] = __float2bfloat16((lane & 1) ? 0.5f - 0.5f * sv : sv);
        asm volatile("fence.proxy.async.shared::cta;" ::: "memory");
        __syncwarp();
        if (lane == 0) mbar_arrive(bar + 8 * B_GS);
        mbar_wait_t(bar + 8 * B_R2FREE, 0);
      }
      G2_ROLE();
#pragma unroll 1
      for (int r = 0; r < 3; r++) {
#pragma unroll
        for (int s = 0; s < 5; s++) {
          const uint32_t fb = bar + 8 * (B_FULL2 + s);
          if (s == 2 && r == 2) break;
          if (r) mbar_wait_t(bar + 8 * (B_EMPTY2 + s), r >> 1);
          else if (s == 1 && has1) mbar_wait_t(bar + 8 * B_G1DONE, 0);
          else if (s == 4 && has1) {
            mbar_wait_t(bar + 8 * B_C2, 0);
            if (WE && elect_one()) tma3(sb + slotO(s), &M.m[mWd], 0, rank * 768 + s * 64, db, fb);
            mbar_wait_t(bar + 8 * B_Z3, 0);
          }
          if (elect_one()) {
#define O_LATE()                                                                                                     \
            _Pragma("unroll") for (int j = ODK; j < 12; j++)                                                         \
              if ((j + ODS < 11 ? j + ODS : 11) == 5 * r + s) tma3(sb + slotO(j % 5), &M.m[mWd], 0, rank * 768 + j * 64, db, bar + 8 * (B_O + j - 8));
            mbar_expect(fb, 5 * r + s < ODK ? 36864 : 28672);
            tma3(sb + slotF(s), &M.m[mWd], 0, rank * 768 + r * 320 + s * 64, db ^ 1, fb);
            if (5 * r + s < ODK && !(WE && s == 4 && r == 0 && has1)) tma3(sb + slotO(s), &M.m[mWd], 0, rank * 768 + r * 320 + s * 64, db, fb);
            if (ODW == 8) { O_LATE() }
            TSL(96 + 5 * r + s);
          }
        }
      }
    } else {
      const int hw = warp - 9;
      if ((sb & 0x3FFFF) != SB0) __trap();
      if (hw == 2) {
        if (lane == 0) { mbar_expect(bar + 8 * B_XCH, 10240); mbar_expect(bar + 8 * (B_XCH + 1), 10240); }
        __syncwarp();
        asm volatile("barrier.cluster.arrive.release.aligned;\nbarrier.cluster.wait.acquire.aligned;" ::: "memory");
      }
      if (has1) {
      {
        const int cq = lane & 3, gl = hw < 2 ? (((tid - 288) >> 2) ^ ((cq & 2) << 1)) + 1 : 0;
        const int cl = hw < 2 ? 0 : lane >> 2;
        uint32_t kp = sb + OFF_H + gl * 160 + cq * 8 + cl * 32, wp = sb + OFF_EX + cq * 32 + cl * 128;
        const uint32_t u1 = sb + OFF_US + cq * 2048 + (15 - gl) * 16, u2 = u1 + 24;
        const uint32_t ua = (cq & 1) && hw < 2 ? u2 : u1, ub = (cq & 1) ? u1 : u2;
        const bool pa0 = (cq & 1) || gl <= 15, pb0 = !(cq & 1) || gl <= 15;
        uint2 vr[8], kr[11];
        uint4 sa, sc;
#define KV_LOAD_K()                                                                                                                                   \
        asm volatile("ld.volatile.shared.v4.u32 {%0,%1,%2,%3}, [%4];" : "=r"(sa.x), "=r"(sa.y), "=r"(sa.z), "=r"(sa.w) : "r"(wp) : "memory");       \
        asm volatile("ld.volatile.shared.v4.u32 {%0,%1,%2,%3}, [%4];" : "=r"(sc.x), "=r"(sc.y), "=r"(sc.z), "=r"(sc.w) : "r"(wp + 16) : "memory");  \
        _Pragma("unroll") for (int r = 0; r < 3; r++) kr[r] = lds64(kp + (r + 5) * 18 * 160);                                                        \
        _Pragma("unroll") for (int r = 0; r < KVA; r++) kr[r + 3] = lds64(kp + (r * 18 + 1) * 160);
#define KV_LOAD_V()                                                                                                                                   \
        _Pragma("unroll") for (int r = KVA; r < 8; r++) kr[r + 3] = lds64(kp + (r * 18 + 1) * 160);                                                  \
        _Pragma("unroll") for (int r = 0; r < KVB; r++) vr[r] = lds64(kp + 23040 + r * 17 * 160);
#define KV_COMPUTE()                                                                                                                                  \
        {                                                                                                                                             \
          const uint32_t wa[4] = {__byte_perm(sa.x, sa.z, 0x5410), __byte_perm(sa.x, sa.z, 0x7632), __byte_perm(sa.y, sa.w, 0x5410), __byte_perm(sa.y, sa.w, 0x7632)}; \
          const uint32_t wb[4] = {__byte_perm(sc.x, sc.z, 0x5410), __byte_perm(sc.x, sc.z, 0x7632), __byte_perm(sc.y, sc.w, 0x5410), __byte_perm(sc.y, sc.w, 0x7632)}; \
          _Pragma("unroll") for (int r = 0; r < 8; r++) {                                                                                             \
            uint32_t x = bmul2(kr[r].x, wa[3]), y = bmul2(kr[r].y, wb[3]);                                                                            \
            if (r + KVB < 8) vr[r + KVB] = lds64(kp + 23040 + (r + KVB) * 17 * 160);                                                                  \
            _Pragma("unroll") for (int j = 1; j < 4; j++) {                                                                                           \
              x = bfma2(kr[r + j].x, wa[3 - j], x);                                                                                                   \
              y = bfma2(kr[r + j].y, wb[3 - j], y);                                                                                                   \
            }                                                                                                                                         \
            vr[r].x = bmul2(x, vr[r].x);                                                                                                              \
            vr[r].y = bmul2(y, vr[r].y);                                                                                                              \
          }                                                                                                                                           \
        }
#define KV_STORE(PA, PB)                                                                                                                              \
        _Pragma("unroll") for (int cc = 0; cc < 4; cc++) {                                                                                            \
          const uint32_t sel = (cc & 1) ? 0x7632 : 0x5410;                                                                                            \
          _Pragma("unroll") for (int p = 0; p < 2; p++) {                                                                                             \
            const int r = 4 - 4 * p;                                                                                                                  \
            const uint32_t qx = (cc & 2) ? __byte_perm(vr[r].y, vr[r + 1].y, sel) : __byte_perm(vr[r].x, vr[r + 1].x, sel);                           \
            const uint32_t qy = (cc & 2) ? __byte_perm(vr[r + 2].y, vr[r + 3].y, sel) : __byte_perm(vr[r + 2].x, vr[r + 3].x, sel);                   \
            if (PA) asm volatile("st.shared.v2.u32 [%0], {%1,%2};" ::"r"(ua + cc * 512 + p * 256), "r"(qx), "r"(qy) : "memory");                      \
            if (PB) asm volatile("st.shared.v2.u32 [%0], {%1,%2};" ::"r"(ub + cc * 512 + p * 256), "r"(qx), "r"(qy) : "memory");                      \
          }                                                                                                                                           \
        }                                                                                                                                             \
        if (!(FK & 1)) asm volatile("fence.proxy.async.shared::cta;" ::: "memory");
        mbar_wait_t(bar + 8 * B_KV, 0);
        if (hw == 0 && lane == 0) TSL(39);
        KV_LOAD_K();
        KV_LOAD_V();
        if (hw < 2) {
#pragma unroll 1
          for (int cb = 0; cb < 5; cb++) {
            if (cb == KVTS && lane == 0) TS(108);
            KVX_AT(0);
            KV_COMPUTE();
            kp += 32;
            wp += 128;
            KV_LOAD_K();
            if (cb == KVTS && lane == 0) TS(109);
            KVX_AT(1);
            bar_sync(5, 96);
            if (cb == KVTS && lane == 0) TS(110);
            if ((FK & 2) && cb == 4 && hw == 0) {
              if (elect_one()) {
                mbar_expect(bar + 8 * B_HLD, 20480);
#pragma unroll
                for (int ch = 0; ch < 5; ch++)
                  bulk_g2s(sb + OFF_H + (2 * ch + 1) * H_PITCH + 224, P.ssm_k + (size_t)(cta * 5 + ch) * 2048, 4096, bar + 8 * B_HLD);
              }
              __syncwarp();
            }
            KVX_AT(2);
            KV_STORE(pa0, pb0);
            if (cb == KVTS && lane == 0) TS(111);
            KVX_AT(3);
            KV_LOAD_V();
            __syncwarp();
            bar_arrive(7, 96);
            if (!CA0 && cb == KVTS && lane == 0) TS(9);
            KVX_AT(4);
          }
        } else {
          KV_COMPUTE();
#pragma unroll 1
          for (int cb = 0; cb < 5; cb++) {
            asm volatile("cp.async.bulk.wait_group.read 0;" ::: "memory");
            bar_sync(5, 96);
            if (!(FK & 2) && cb == 4 && elect_one()) {
              mbar_expect(bar + 8 * B_HLD, 20480);
#pragma unroll
              for (int ch = 0; ch < 5; ch++)
                bulk_g2s(sb + OFF_H + (2 * ch + 1) * H_PITCH + 224, P.ssm_k + (size_t)(cta * 5 + ch) * 2048, 4096, bar + 8 * B_HLD);
            }
            KV_STORE(cl == cb, false);
            __syncwarp();
            bar_sync(7, 96);
            if (FK & 1) asm volatile("fence.proxy.async.shared::cta;" ::: "memory");
            if (!(NOKV & 2) && elect_one()) tma2_store(&M.m[mU], sb + OFF_US, 1920 - 128 * (cta >> 3), (cta & 7) * 160 + cb * 32);
            asm volatile("cp.async.bulk.commit_group;" ::: "memory");
          }
        }
        if (lane == 0) TS(54 + hw);
        if (hw == 2) {
          asm volatile("cp.async.bulk.wait_group 0;" ::: "memory");
          __syncwarp();
          if (lane == 0) { flag_add(&g_cnt[(C_U + (cta & 7)) * 32]); TS(40); }
          flag_wait(&g_cnt[(C_U + mb) * 32], &g_cnt[(C_U + mb) * 32], 16);
          if (lane == 0) TS(32);
          mbar_wait_t(bar + 8 * B_R2FREE, 0);
          if (elect_one()) {
#pragma unroll
            for (int ch = 0; ch < 5; ch++) {
              mbar_expect(bar + 8 * (B_UFULL + ch), 8192 + (FCP ? 4080 : 0));
              bulk_g2s(sb + OFF_U + (4 - ch) * 8192, g_U + (size_t)(5 * cta + ch) * 4096, 8192, bar + 8 * (B_UFULL + ch));
            }
            TSL(33);
          }
        }
      }
      if (hw < 2) {
        int ht;
        asm volatile("mov.u32 %0, %%tid.x;" : "=r"(ht));
        ht -= 288;
        const int lane = ht & 31;
        for (int i = ht; i < 10 * 15; i += 64) {
          const int b = i / 15, e = i % 15;
          if (e < 14) *reinterpret_cast<uint4*>(sm + OFF_H + b * H_PITCH + e * 16) = make_uint4(0u, 0u, 0u, 0u);
          else if ((b & 1) == 0) *reinterpret_cast<uint2*>(sm + OFF_H + b * H_PITCH + 224) = make_uint2(0u, 0u);
        }
        const float dv = lane < 5 ? __bfloat162float(P.ssm_D[cta * 5 + lane]) : 0.f;
        __syncwarp();
        mbar_wait_t(bar + 8 * B_HLD, 0);
        if (hw == 0) {
          if (lane < 5) {
            __nv_bfloat16* h0 = reinterpret_cast<__nv_bfloat16*>(sm + OFF_H + (2 * lane + 1) * H_PITCH + 224);
            *h0 = __float2bfloat16(__bfloat162float(*h0) + dv);
          }
          __syncwarp();
        }
#pragma unroll 1
        for (int b = 0; b < 5; b++) {
          unsigned char* dst = sm + OFF_H + b * 2 * H_PITCH + (ht & 32) * 64 + 232 + lane * 8;
          uint2 hv[8];
#pragma unroll
          for (int u = 0; u < 8; u++) if (!(NOKV & 4)) hv[u] = *reinterpret_cast<const uint2*>(dst + H_PITCH - 8 + u * 256);
#pragma unroll
          for (int u = 0; u < 8; u++) if (!(NOKV & 4)) *reinterpret_cast<uint2*>(dst + u * 256) = hv[u];
          asm volatile("fence.proxy.async.shared::cta;" ::: "memory");
          __syncwarp();
          if (lane == 0) mbar_arrive(bar + 8 * (B_UFULL + b));
        }
        if (hw == 1 && lane == 0) TSL(41);
      }
      }
      G2_ROLE();
      const int ga = 20 * tb, gb = ga + 19;
      const unsigned* fa = &g_cnt[(C_H + 2 * ((ga / 130) * 4 + min((ga % 130) >> 5, 3))) * 32];
      const unsigned* fb = &g_cnt[(C_H + 2 * ((gb / 130) * 4 + min((gb % 130) >> 5, 3))) * 32];
      if (hw == 0) {
        const __nv_bfloat16* hsrc = g_Hs + (size_t)(rank * 24 * NGRP + ga) * 256;
        if (has1) mbar_wait_t(bar + 8 * B_HDR, 0);
        if (lane == 0) TS(25);
        flag_wait(fa + rank * 32, fb + rank * 32, 8);
        if (lane == 0) TS(34);
#pragma unroll 1
        for (int r = 0; r < 3; r++) {
#pragma unroll
          for (int s = 0; s < 5; s++) {
            if (s == 2 && r == 2) break;
            if (r) mbar_wait_t(bar + 8 * (B_EMPTY2 + s), r >> 1);
            else if (s == 3 && has1) { mbar_wait_t(bar + 8 * (B_CD + 0), 0); mbar_wait_t(bar + 8 * (B_CD + 1), 0); }
            else if (s == 4 && has1) mbar_wait_t(bar + 8 * B_C2, 0);
            if (elect_one()) {
              bulk_g2s(sb + slotB0(s), hsrc + s * (2 * NGRP * 256), 10240, bar + 8 * (B_FULL2 + s));
              bulk_g2s(sb + slotB1(s), hsrc + s * (2 * NGRP * 256) + NGRP * 256, 10240, bar + 8 * (B_FULL2 + s));
              if (ODW == 9) { O_LATE() }
              TS(112 + 5 * r + s);
            }
          }
          hsrc += 10 * NGRP * 256;
        }
      } else if (hw == 1) {
        if (elect_one()) { prefetch_map(&M.m[mQ]); prefetch_map(&M.m[mZ]); prefetch_map(&M.m[mO]); }
        flag_wait(fa, fb, 8);
        flag_wait(fa + 32, fb + 32, 8);
        if (elect_one()) {
          mbar_expect(bar + 8 * B_QG, 20480 + 640);
          bulk_g2s(sb + OFF_G, g_gate + ga * 8, 640, bar + 8 * B_QG);
          mbar_expect(bar + 8 * B_Z, 20480);
        }
#pragma unroll 1
        for (int hf = 0; hf < 2; hf++) {
          if (has1) { mbar_wait_t(bar + 8 * (hf ? B_C4 : B_C2), 0); mbar_wait_t(bar + 8 * (QE && !hf ? B_CD + 3 : B_Z3), 0); }
          if (elect_one()) { tma4(sb + OFF_Q + hf * 10240, &M.m[mQ], db * 64, 0, ((2 * tb + hf) % 13) * 10, (2 * tb + hf) / 13, bar + 8 * B_QG); TS(110 + hf); }
        }
        flag_wait(&g_cnt[(C_Z + db) * 32], &g_cnt[(C_Z + db) * 32], (64 * db + 63) / 5 - (64 * db) / 5 + 1);
        if (lane == 0) TS(109);
        mbar_wait_t(bar + 8 * (ZN ? B_ZD : B_ZF), 0);
        if (elect_one()) {
#pragma unroll
          for (int b = 0; b < (ZN ? 8 : 1); b++) tma2(sb + zbox(b), &M.m[mZ], tb * 160, db * 64 + 8 * b, bar + 8 * B_Z);
          TSL(35);
        }
        if (ZN) mbar_wait_t(bar + 8 * B_ZF, 0);
        if (lane == 0 && atomicAdd(&g_cnt[C_DONE * 32], 1u) == NCTA - 1) {
          for (int i = 0; i < C_COUNT; i++) g_cnt[i * 32] = 0;
        }
      } else {
        if (has1) {
          const int g0 = (mb >> 2) * 130 + (mb & 3) * 32;
          mbar_wait_t(bar + 8 * B_GS, 0);
          if (elect_one()) bulk_s2g(g_gate + (g0 + 2 * ft) * 8, sb + OFF_GS, 64);
#pragma unroll 1
          for (int j = 0; j < 4; j++) {
            const int i = (j >> 1) | ((j & 1) << 1);
            mbar_wait_t(bar + 8 * (B_SIGH + i), 0);
            if ((FC >> (i & 1)) & 1) asm volatile("fence.proxy.async.shared::cta;" ::: "memory");
            if (elect_one()) {
              tma3_store(&M.m[mH], sb + i * 8192, 0, 3 * ft, g0 + 8 * i);
              tma3_store(&M.m[mH], sb + G1_STAGE + i * 8192, 0, 3 * ft, g0 + 8 * i + 4);
            }
          }
          asm volatile("cp.async.bulk.commit_group;" ::: "memory");
          asm volatile("cp.async.bulk.wait_group.read 0;" ::: "memory");
          __syncwarp();
          if (lane == 0) { mbar_arrive(bar + 8 * B_HDR); TSL(45); }
          asm volatile("cp.async.bulk.wait_group 0;" ::: "memory");
          __syncwarp();
          if (lane == 0) { flag_add(&g_cnt[(C_H + 2 * mb + (ft >> 3)) * 32]); TS(42); }
#pragma unroll 1
          for (int j = 0; j < 5; j++) {
            const int ch = j < 4 ? j ^ 1 : 4;
            __nv_bfloat16* zd = g_zT + (size_t)(5 * cta + ch) * (NGRP * 8);
            mbar_wait_t(bar + 8 * (B_SIGZ + ch), 0);
            if ((FZ >> ch) & 1) asm volatile("fence.proxy.async.shared::cta;" ::: "memory");
            if (elect_one()) bulk_s2g(zd, sb + zstage(ch), NGRP * 16);
            if (j == 2) {
              asm volatile("cp.async.bulk.commit_group;" ::: "memory");
              asm volatile("cp.async.bulk.wait_group.read 0;" ::: "memory");
              __syncwarp();
              if (lane < 2) mbar_arrive(bar + 8 * B_Z3);
              if (lane == 0) TS(108);
            }
          }
          asm volatile("cp.async.bulk.commit_group;" ::: "memory");
          asm volatile("cp.async.bulk.wait_group 0;" ::: "memory");
          __syncwarp();
          if (lane == 0) flag_add(&g_cnt[(C_Z + (5 * cta) / 64) * 32]);
          if (lane == 0 && (5 * cta) / 64 != (5 * cta + 4) / 64) flag_add(&g_cnt[(C_Z + (5 * cta + 4) / 64) * 32]);
          if (lane == 0) TSL(43);
        }
        if (ZN && lane == 0) mbar_arrive(bar + 8 * B_ZD);
        mbar_wait_t(bar + 8 * B_QC, 0);
        if (lane == 0) asm volatile("mbarrier.arrive.relaxed.cluster.shared::cluster.b64 _, [%0];" ::"r"(peer_addr(bar + 8 * B_XF)) : "memory");
      }
    }
  }
}

typedef CUresult (*EncFn)(CUtensorMap*, CUtensorMapDataType, cuuint32_t, void*, const cuuint64_t*, const cuuint64_t*,
                          const cuuint32_t*, const cuuint32_t*, CUtensorMapInterleave, CUtensorMapSwizzle,
                          CUtensorMapL2promotion, CUtensorMapFloatOOBfill);

void make_map(EncFn enc, CUtensorMap* m, const void* ptr, int rank, const cuuint64_t* dims, const cuuint64_t* str,
              const cuuint32_t* box, CUtensorMapSwizzle sw, int pr = 2) {
  const cuuint32_t es[5] = {1, 1, 1, 1, 1};
  enc(m, CU_TENSOR_MAP_DATA_TYPE_BFLOAT16, rank, const_cast<void*>(ptr), dims, str, box, es, CU_TENSOR_MAP_INTERLEAVE_NONE,
      sw, static_cast<CUtensorMapL2promotion>(pr), CU_TENSOR_MAP_FLOAT_OOB_FILL_NONE);
}

__global__ void probe_kernel() {}

void cluster_order(unsigned char* perm) {
  constexpr int NP = NCTA / 2;
  for (int c = 0; c < NP; c++) perm[c] = c;
  int n[9] = {0};
  cudaFuncSetAttribute(probe_kernel, cudaFuncAttributeMaxDynamicSharedMemorySize, SMEM_BYTES);
  cudaFuncSetAttribute(probe_kernel, cudaFuncAttributeNonPortableClusterSizeAllowed, 1);
  for (int k = 1; k <= 8; k++) {
    cudaLaunchConfig_t cfg = {};
    cudaLaunchAttribute at;
    at.id = cudaLaunchAttributeClusterDimension;
    at.val.clusterDim.x = 2 * k; at.val.clusterDim.y = 1; at.val.clusterDim.z = 1;
    cfg.gridDim = dim3(16 * k); cfg.blockDim = dim3(384); cfg.dynamicSmemBytes = SMEM_BYTES;
    cfg.attrs = &at; cfg.numAttrs = 1;
    if (cudaOccupancyMaxActiveClusters(&n[k], probe_kernel, &cfg) != cudaSuccess) { cudaGetLastError(); return; }
  }
  int R[9];
  R[7] = n[8]; R[6] = n[7]; R[5] = n[6]; R[4] = n[5]; R[3] = n[4] - n[8];
  R[0] = R[1] = R[2] = n[2] - R[3] - R[5] - R[7];
  R[8] = n[3] - R[2] - R[5];
  int lone = n[1];
  for (int r = 0; r < 9; r++) {
    if (R[r] < 0 || R[r] > 16 || (r && R[r] > R[r - 1])) return;
    lone -= R[r];
  }
  if (lone < 0 || n[1] < NP) return;
  int gpc[NP], rnd[NP];
  for (int c = 0, r = 0, pos = 0; c < NP; c++) {
    if (c < lone) { gpc[c] = -1; rnd[c] = 8; continue; }
    while (pos >= R[r]) { pos = 0; r++; }
    gpc[c] = R[0] - R[r] + pos++; rnd[c] = r;
  }
  int m = 0;
  for (int g = R[0] - 1; g >= 0; g--)
    for (int c = 0; c < NP; c++) if (gpc[c] == g && rnd[c] < 8) perm[c] = m++;
  for (int c = NP - 1; c >= 0; c--) if (rnd[c] == 8) perm[c] = m++;
}

}

extern "C" void kernel_launch(void* const* d_in, const int* in_sizes, int n_in, void* d_out, int out_size) {
  (void)in_sizes; (void)n_in; (void)out_size;
  static EncFn enc = nullptr;
  static unsigned char perm[NCTA / 2];
  static void *zT = nullptr, *uT = nullptr, *hT = nullptr;
  if (!enc) {
    cudaDriverEntryPointQueryResult qr;
    cudaGetDriverEntryPoint("cuTensorMapEncodeTiled", (void**)&enc, cudaEnableDefault, &qr);
    cudaGetSymbolAddress(&zT, g_zT);
    cudaGetSymbolAddress(&uT, g_U);
    cudaGetSymbolAddress(&hT, g_Hs);
    cudaFuncSetAttribute(fused_kernel, cudaFuncAttributeMaxDynamicSharedMemorySize, SMEM_BYTES);
    cluster_order(perm);
  }
  Maps M;
  {
    const cuuint64_t dims[4] = {640, 8, 128, 2}, str[3] = {128 * 1280, 1280, 1024 * 1280};
    const cuuint32_t b1[4] = {64, 8, 32, 1}, b2[4] = {64, 8, 10, 1};
    make_map(enc, &M.m[mX], d_in[0], 4, dims, str, b1, CU_TENSOR_MAP_SWIZZLE_128B, PRX);
    make_map(enc, &M.m[mQ], d_in[0], 4, dims, str, b2, CU_TENSOR_MAP_SWIZZLE_128B);
    make_map(enc, &M.m[mO], d_out, 4, dims, str, b2, CU_TENSOR_MAP_SWIZZLE_128B);
  }
  {
    const cuuint64_t dims[3] = {32, 640, 48}, str[2] = {3072, 64};
    const cuuint32_t box[3] = {32, WH ? 32 : 64, 3};
    make_map(enc, &M.m[mWg], d_in[7], 3, dims, str, box, CU_TENSOR_MAP_SWIZZLE_64B, PRW);
    make_map(enc, &M.m[mWu], d_in[8], 3, dims, str, box, CU_TENSOR_MAP_SWIZZLE_64B, PRW);
  }
  {
    const cuuint64_t dims[3] = {64, 1536, 10}, str[2] = {1280, 128};
    const cuuint32_t box[3] = {64, 64, 1};
    make_map(enc, &M.m[mWd], d_in[9], 3, dims, str, box, CU_TENSOR_MAP_SWIZZLE_128B, PRD);
  }
  {
    const cuuint64_t dims[2] = {NGRP * 8, 640}, str[1] = {NGRP * 16};
    const cuuint32_t box[2] = {160, ZN ? 8 : 64};
    make_map(enc, &M.m[mZ], zT, 2, dims, str, box, CU_TENSOR_MAP_SWIZZLE_NONE, PRH);
  }
  {
    const cuuint64_t dims[3] = {256, 48, NGRP}, str[2] = {NGRP * 512, 512};
    const cuuint32_t box[3] = {256, 3, 4};
    make_map(enc, &M.m[mH], hT, 3, dims, str, box, CU_TENSOR_MAP_SWIZZLE_NONE, PRH);
  }
  {
    const cuuint64_t dims[3] = {640, 256, 8}, str[2] = {8 * 1280, 1280};
    const cuuint32_t bk[3] = {80, 18, 8}, bv[3] = {80, 17, 8};
    make_map(enc, &M.m[mK], d_in[1], 3, dims, str, bk, CU_TENSOR_MAP_SWIZZLE_NONE, PRK);
    make_map(enc, &M.m[mV], d_in[2], 3, dims, str, bv, CU_TENSOR_MAP_SWIZZLE_NONE, PRK);
  }
  {
    const cuuint64_t dims[2] = {2048, 1280}, str[1] = {4096};
    const cuuint32_t box[2] = {128, 32};
    make_map(enc, &M.m[mU], uT, 2, dims, str, box, CU_TENSOR_MAP_SWIZZLE_NONE);
  }
  Params P;
  P.q = (const __nv_bfloat16*)d_in[0]; P.k = (const __nv_bfloat16*)d_in[1]; P.v = (const __nv_bfloat16*)d_in[2];
  P.w_gate = (const __nv_bfloat16*)d_in[7]; P.w_up = (const __nv_bfloat16*)d_in[8]; P.w_down = (const __nv_bfloat16*)d_in[9];
  P.shift_k = (const __nv_bfloat16*)d_in[3]; P.ssm_k = (const __nv_bfloat16*)d_in[4]; P.ssm_D = (const __nv_bfloat16*)d_in[5];
  P.gate_w = (const __nv_bfloat16*)d_in[10];
  for (int c = 0; c < NCTA / 2; c++) {
    const int p2 = perm[c];
    P.c2[c] = (p2 & 64) + (((p2 >> 1) & 4) | (p2 & 3)) * 8 + (((p2 >> 3) & 6) | ((p2 >> 2) & 1));
    P.g2[c] = (p2 / 5) << 3 | (p2 % 5);
    P.q0 = P.q;
    P.m4[c >> 1] = (c & 1) ? P.m4[c >> 1] | (P.c2[c] >> 3) << 4 : P.c2[c] >> 3;
  }
  fused_kernel<<<NCTA, 384, SMEM_BYTES>>>(P, M);
}
```
